```python
import torch

def _softmax(x, axis=-1):
    return torch.softmax(x, dim=axis)
def _gelu(x):
    return torch.nn.functional.gelu(x, approximate="tanh")
def _silu(x):
    return torch.nn.functional.silu(x)
def _sigmoid(x):
    return torch.sigmoid(x)
def _layernorm(x, axis=-1, eps=1e-5):
    m = x.mean(dim=axis, keepdim=True)
    v = x.var(dim=axis, keepdim=True, unbiased=False)
    return (x - m) / torch.sqrt(v + eps)
def _scatter_add(tgt, idx, src, axis=0):
    return tgt.clone().index_add_(axis, idx, src)
def _segment_sum(src, seg, n):
    out = torch.zeros((n,) + src.shape[1:], dtype=src.dtype)
    return out.index_add_(0, seg, src)
def _pad(x, pw):
    flat = tuple(v for pair in reversed(pw) for v in pair)
    return torch.nn.functional.pad(x, flat)

kernel_name = 'sequential_preLN__spectral_gfnet__dense_activation_silu__prompt'

def setup_inputs():

    _w = (lambda a: (lambda t: t.to(torch.bfloat16) if t.is_floating_point() else t)(torch.as_tensor(a)))
    def _A_setup():
        B, S, D = 1, 2048, 512
        Df = D // 2 + 1
        return {
            "x": _w((lambda *s: torch.randn(*s, dtype=torch.bfloat16) * 0.05)(B, S, D)),
            "w_r": _w((lambda *s: torch.randn(*s, dtype=torch.bfloat16) * 0.4)(S, Df) * 0.02),
            "w_i": _w((lambda *s: torch.randn(*s, dtype=torch.bfloat16) * 0.4)(S, Df) * 0.02),
        }
    _A_in = _A_setup()

    def _B_setup():
        B, S, D, F = 1, 2048, 512, 1792
        return {
            "x": _w((lambda *s: torch.randn(*s, dtype=torch.bfloat16) * 0.05)(B, S, D)),
            "w1": _w((lambda *s: torch.randn(*s, dtype=torch.bfloat16) * 0.8)(D, F) * (D ** -0.5)),
            "w2": _w((lambda *s: torch.randn(*s, dtype=torch.bfloat16) * 0.1)(F, D) * (F ** -0.5)),
        }
    _B_in = _B_setup()

    return {
        "A_x": _A_in["x"],
        "A_w_r": _A_in["w_r"],
        "A_w_i": _A_in["w_i"],
        "B_x": _B_in["x"],
        "B_w1": _B_in["w1"],
        "B_w2": _B_in["w2"],
    }

def reference(A_x, A_w_r, A_w_i, B_x, B_w1, B_w2):
    def _A_ref(x, w_r, w_i):
        B, S, D = x.shape
        X = (lambda x, axes=(-2,-1): torch.fft.rfft2(x.float(), dim=axes))(x, axes=(-2, -1))
        W = w_r + 1j * w_i
        X = X * W
        y = (lambda x, s, axes=(-2,-1): torch.fft.irfft2(x, s=s, dim=axes).to(torch.bfloat16))(X, (S, D), axes=(-2, -1))
        return y

    def _B_ref(x, w1, w2):
        h = torch.einsum("bsd,df->bsf", x, w1)
        h = _silu(h)
        out = torch.einsum("bsf,fd->bsd", h, w2)
        return out

    x = A_x
    h = x + _A_ref(_layernorm(x, axis=-1), A_w_r, A_w_i)
    h2 = h + _B_ref(_layernorm(h, axis=-1), B_w1, B_w2)
    return h2
```

```cpp
#include <cuda_runtime.h>
#include <cuda_bf16.h>
#include <cuda.h>
#include <stdint.h>

namespace {
constexpr int DF = 257;
constexpr int NCTA = 128;
constexpr int WSLOT = 28672, NW = 6, ASLOT = 8192, NA = 3;
constexpr int OFF_A = NW * WSLOT;
constexpr int OFF_TAB = OFF_A;
constexpr int NG_P1 = 17, NG_ALL = 51;
constexpr int OFF_X = OFF_A + NG_ALL * 512;
constexpr int OFF_WF = (NW - 1) * WSLOT;
constexpr int OFF_WRAW = (NW - 2) * WSLOT;
constexpr int OFF_XS = (NW - 3) * WSLOT;
constexpr int OFF_BAR = OFF_A + 2 * NA * ASLOT;
constexpr int SMEM_BYTES = OFF_BAR + 1024 + 1024;
constexpr int LAG = 3, RL0 = 7, RL1 = 5, SG = 7, HS = 5;
constexpr int DELAY0 = 1300, DELAY5 = 1800, DELAY1 = 1300, DELAY2 = 800, DELAY3 = 900, DELAY4 = 400;
__device__ __align__(128) const uint32_t g_tab[NG_ALL * 128] = {
0x3f803f80,0xbf803f80,0x3f803f80,0xbf803f80,0x3f803f80,0xbf803f80,0x3f803f80,0xbf803f80,0x3f803f80,0xbf803f80,0x3f803f80,0xbf803f80,0x3f803f80,0xbf803f80,0x3f803f80,0xbf803f80,
0x3f6d3f80,0xbec40000,0xbf6dbf80,0x3ec40000,0x3ec43f35,0xbf6dbf35,0xbec4bf35,0x3f6d3f35,0xbec40000,0xbf6dbf80,0x3ec40000,0x3f6d3f80,0xbf6dbf35,0xbec4bf35,0x3f6d3f35,0x3ec43f35,
0x3f353f80,0xbf350000,0x3f353f80,0xbf350000,0xbf350000,0xbf35bf80,0xbf350000,0xbf35bf80,0xbf35bf80,0x3f350000,0xbf35bf80,0x3f350000,0x3f350000,0x3f353f80,0x3f350000,0x3f353f80,
0x3ec43f80,0xbf6d0000,0xbec4bf80,0x3f6d0000,0xbf6dbf35,0x3ec4bf35,0x3f6d3f35,0xbec43f35,0x3f6d0000,0x3ec43f80,0xbf6d0000,0xbec4bf80,0xbec43f35,0xbf6dbf35,0x3ec4bf35,0x3f6d3f35,
0x3f80,0xbf800000,0x3f80,0xbf800000,0xbf80,0x3f800000,0xbf80,0x3f800000,0x3f80,0xbf800000,0x3f80,0xbf800000,0xbf80,0x3f800000,0xbf80,0x3f800000,
0xbec43f80,0xbf6d0000,0x3ec4bf80,0x3f6d0000,0x3f6dbf35,0x3ec43f35,0xbf6d3f35,0xbec4bf35,0xbf6d0000,0x3ec4bf80,0x3f6d0000,0xbec43f80,0x3ec43f35,0xbf6d3f35,0xbec4bf35,0x3f6dbf35,
0xbf353f80,0xbf350000,0xbf353f80,0xbf350000,0x3f350000,0xbf353f80,0x3f350000,0xbf353f80,0x3f35bf80,0x3f350000,0x3f35bf80,0x3f350000,0xbf350000,0x3f35bf80,0xbf350000,0x3f35bf80,
0xbf6d3f80,0xbec40000,0x3f6dbf80,0x3ec40000,0xbec43f35,0xbf6d3f35,0x3ec4bf35,0x3f6dbf35,0x3ec40000,0xbf6d3f80,0xbec40000,0x3f6dbf80,0x3f6dbf35,0xbec43f35,0xbf6d3f35,0x3ec4bf35,
0x3f800000,0x3f800000,0x0,0x0,0x3f800000,0x3f800000,0x0,0x0,0x3f800000,0x3f800000,0x0,0x0,0x3f800000,0x3f800000,0x0,0x0,
0x3f800000,0x3f7fb10f,0x0,0x3d48fb30,0x3f7ec46d,0x3f7d3aac,0x3dc8bd36,0x3e164083,0x3f7b14be,0x3f7853f8,0x3e47c5c2,0x3e78cfcc,0x3f74fa0b,0x3f710908,0x3e94a031,0x3eac7cd4,
0x3f800000,0x3f7ec46d,0x0,0x3dc8bd36,0x3f7b14be,0x3f74fa0b,0x3e47c5c2,0x3e94a031,0x3f6c835e,0x3f61c598,0x3ec3ef15,0x3ef15aea,0x3f54db31,0x3f45e403,0x3f0e39da,0x3f226799,
0x3f800000,0x3f7d3aac,0x0,0x3e164083,0x3f74fa0b,0x3f676bd8,0x3e94a031,0x3edae880,0x3f54db31,0x3f3daef9,0x3f0e39da,0x3f2beb4a,0x3f226799,0x3f039c3d,0x3f45e403,0x3f5b941a,
0x3f800000,0x3f7b14be,0x0,0x3e47c5c2,0x3f6c835e,0x3f54db31,0x3ec3ef15,0x3f0e39da,0x3f3504f3,0x3f0e39da,0x3f3504f3,0x3f54db31,0x3ec3ef15,0x3e47c5c2,0x3f6c835e,0x3f7b14be,
0x3f800000,0x3f7853f8,0x0,0x3e78cfcc,0x3f61c598,0x3f3daef9,0x3ef15aea,0x3f2beb4a,0x3f0e39da,0x3eac7cd4,0x3f54db31,0x3f710908,0x3dc8bd36,0xbe164083,0x3f7ec46d,0x3f7d3aac,
0x3f800000,0x3f74fa0b,0x0,0x3e94a031,0x3f54db31,0x3f226799,0x3f0e39da,0x3f45e403,0x3ec3ef15,0x3dc8bd36,0x3f6c835e,0x3f7ec46d,0xbe47c5c2,0xbef15aea,0x3f7b14be,0x3f61c598,
0x3f800000,0x3f710908,0x0,0x3eac7cd4,0x3f45e403,0x3f039c3d,0x3f226799,0x3f5b941a,0x3e47c5c2,0xbe164083,0x3f7b14be,0x3f7d3aac,0xbef15aea,0xbf3daef9,0x3f61c598,0x3f2beb4a,
0x3f800000,0x3f800000,0x0,0x0,0x3f800000,0x3f800000,0x0,0x0,0x3f800000,0x3f800000,0x0,0x0,0x3f800000,0x3f800000,0x0,0x0,
0x3f7ffb11,0x3f7f84ab,0x3c490e90,0x3d7b2b74,0x3f7e70b0,0x3f7cbfc9,0x3de1bc2e,0x3e22abb6,0x3f7a7302,0x3f778bc5,0x3e541501,0x3e827dc0,0x3f740bdd,0x3f6ff573,0x3e9aa086,0x3eb263ef,
0x3f7fec43,0x3f7e1324,0x3cc90ab0,0x3dfab273,0x3f79c79d,0x3f731447,0x3e605c13,0x3ea09ae5,0x3f6a09a7,0x3f5ebe05,0x3ecf7bca,0x3efc5d27,0x3f514d3d,0x3f41d870,0x3f13682a,0x3f273656,
0x3f7fd397,0x3f7baccd,0x3d16c32c,0x3e3b6ecf,0x3f721352,0x3f633c5a,0x3ea68f12,0x3eebcbbb,0x3f4f7a1f,0x3f373a23,0x3f15f6d9,0x3f32c8c9,0x3f1b02c6,0x3ef6e0cb,0x3f4bbbf8,0x3f604621,
0x3f7fb10f,0x3f7853f8,0x3d48fb30,0x3e78cfcc,0x3f676bd8,0x3f4d9f02,0x3edae880,0x3f187fc0,0x3f2beb4a,0x3f039c3d,0x3f3daef9,0x3f5b941a,0x3eac7cd4,0x3e164083,0x3f710908,0x3f7d3aac,
0x3f7f84ab,0x3f740bdd,0x3d7b2b74,0x3e9aa086,0x3f59f26a,0x3f32c8c9,0x3f064b82,0x3f373a23,0x3f00e7e4,0x3e8e9a22,0x3f5d2d53,0x3f75dec6,0x3d16c32c,0xbe541501,0x3f7fd397,0x3f7a7302,
0x3f7f4e6d,0x3f6ed89e,0x3d96a905,0x3eb8442a,0x3f49d112,0x3f13682a,0x3f1d7fd1,0x3f514d3d,0x3ea09ae5,0x3cc90ab0,0x3f731447,0x3f7fec43,0xbe888e93,0xbf08f59b,0x3f76ba07,0x3f584853,
0x3f7f0e58,0x3f68bf3c,0x3dafb680,0x3ed53641,0x3f373a23,0x3ee0924f,0x3f32c8c9,0x3f660f88,0x3de1bc2e,0xbe6c9a7f,0x3f7e70b0,0x3f791298,0xbf0b9a6b,0xbf4bbbf8,0x3f5695e5,0x3f1b02c6,
0x3f800000,0x3f800000,0x0,0x0,0x3f800000,0x3f800000,0x0,0x0,0x3f800000,0x3f800000,0x0,0x0,0x3f800000,0x3f800000,0x0,0x0,
0x3f7fec43,0x3f7f4e6d,0x3cc90ab0,0x3d96a905,0x3f7e1324,0x3f7c3b28,0x3dfab273,0x3e2f10a2,0x3f79c79d,0x3f76ba07,0x3e605c13,0x3e888e93,0x3f731447,0x3f6ed89e,0x3ea09ae5,0x3eb8442a,
0x3f7fb10f,0x3f7d3aac,0x3d48fb30,0x3e164083,0x3f7853f8,0x3f710908,0x3e78cfcc,0x3eac7cd4,0x3f676bd8,0x3f5b941a,0x3edae880,0x3f039c3d,0x3f4d9f02,0x3f3daef9,0x3f187fc0,0x3f2beb4a,
0x3f7f4e6d,0x3f79c79d,0x3d96a905,0x3e605c13,0x3f6ed89e,0x3f5ebe05,0x3eb8442a,0x3efc5d27,0x3f49d112,0x3f3085bb,0x3f1d7fd1,0x3f396842,0x3f13682a,0x3ee63375,0x3f514d3d,0x3f64aa59,
0x3f7ec46d,0x3f74fa0b,0x3dc8bd36,0x3e94a031,0x3f61c598,0x3f45e403,0x3ef15aea,0x3f226799,0x3f226799,0x3ef15aea,0x3f45e403,0x3f61c598,0x3e94a031,0x3dc8bd36,0x3f74fa0b,0x3f7ec46d,
0x3f7e1324,0x3f6ed89e,0x3dfab273,0x3eb8442a,0x3f514d3d,0x3f273656,0x3f13682a,0x3f41d870,0x3ee63375,0x3e605c13,0x3f64aa59,0x3f79c79d,0xbcc90ab0,0xbe888e93,0x3f7fec43,0x3f76ba07,
0x3f7d3aac,0x3f676bd8,0x3e164083,0x3edae880,0x3f3daef9,0x3f039c3d,0x3f2beb4a,0x3f5b941a,0x3e78cfcc,0xbd48fb30,0x3f7853f8,0x3f7fb10f,0xbeac7cd4,0xbf187fc0,0x3f710908,0x3f4d9f02,
0x3f7c3b28,0x3f5ebe05,0x3e2f10a2,0x3efc5d27,0x3f273656,0x3eb8442a,0x3f41d870,0x3f6ed89e,0x3cc90ab0,0xbea09ae5,0x3f7fec43,0x3f731447,0xbf1d7fd1,0xbf584853,0x3f49d112,0x3f08f59b,
0x3f800000,0x3f800000,0x0,0x0,0x3f800000,0x3f800000,0x0,0x0,0x3f800000,0x3f800000,0x0,0x0,0x3f800000,0x3f800000,0x0,0x0,
0x3f7fd397,0x3f7f0e58,0x3d16c32c,0x3dafb680,0x3f7dabcc,0x3f7baccd,0x3e09cf86,0x3e3b6ecf,0x3f791298,0x3f75dec6,0x3e6c9a7f,0x3e8e9a22,0x3f721352,0x3f6db293,0x3ea68f12,0x3ebe1d4a,
0x3f7f4e6d,0x3f7c3b28,0x3d96a905,0x3e2f10a2,0x3f76ba07,0x3f6ed89e,0x3e888e93,0x3eb8442a,0x3f64aa59,0x3f584853,0x3ee63375,0x3f08f59b,0x3f49d112,0x3f396842,0x3f1d7fd1,0x3f3085bb,
0x3f7e70b0,0x3f778bc5,0x3de1bc2e,0x3e827dc0,0x3f6b4b0c,0x3f59f26a,0x3ec9b953,0x3f064b82,0x3f43e200,0x3f299415,0x3f24d225,0x3f3fc767,0x3f0b9a6b,0x3ed53641,0x3f5695e5,0x3f68bf3c,
0x3f7d3aac,0x3f710908,0x3e164083,0x3eac7cd4,0x3f5b941a,0x3f3daef9,0x3f039c3d,0x3f2beb4a,0x3f187fc0,0x3edae880,0x3f4d9f02,0x3f676bd8,0x3e78cfcc,0x3d48fb30,0x3f7853f8,0x3f7fb10f,
0x3f7baccd,0x3f68bf3c,0x3e3b6ecf,0x3ed53641,0x3f47de65,0x3f1b02c6,0x3f1ff6cb,0x3f4bbbf8,0x3ec9b953,0x3e22abb6,0x3f6b4b0c,0x3f7cbfc9,0xbdafb680,0xbea68f12,0x3f7f0e58,0x3f721352,
0x3f79c79d,0x3f5ebe05,0x3e605c13,0x3efc5d27,0x3f3085bb,0x3ee63375,0x3f396842,0x3f64aa59,0x3e2f10a2,0xbdfab273,0x3f7c3b28,0x3f7e1324,0xbecf7bca,0xbf273656,0x3f6a09a7,0x3f41d870,
0x3f778bc5,0x3f531849,0x3e827dc0,0x3f10d3cd,0x3f15f6d9,0x3e8e9a22,0x3f4f7a1f,0x3f75dec6,0xbd7b2b74,0xbec9b953,0x3f7f84ab,0x3f6b4b0c,0xbf2e3bde,0xbf633c5a,0x3f3b8f3b,0x3eebcbbb,
0x3f803f80,0x0,0x3f803f80,0x0,0x3f803f80,0x0,0x3f803f80,0x0,0x3f803f80,0x0,0x3f803f80,0x0,0x3f803f80,0x0,0x3f803f80,0x0,
0x3f353f80,0x3f350000,0x3f353f80,0x3f350000,0xbf350000,0x3f353f80,0xbf350000,0x3f353f80,0xbf35bf80,0xbf350000,0xbf35bf80,0xbf350000,0x3f350000,0xbf35bf80,0x3f350000,0xbf35bf80,
0x3f80,0x3f800000,0x3f80,0x3f800000,0xbf80,0xbf800000,0xbf80,0xbf800000,0x3f80,0x3f800000,0x3f80,0x3f800000,0xbf80,0xbf800000,0xbf80,0xbf800000,
0xbf353f80,0x3f350000,0xbf353f80,0x3f350000,0x3f350000,0x3f35bf80,0x3f350000,0x3f35bf80,0x3f35bf80,0xbf350000,0x3f35bf80,0xbf350000,0xbf350000,0xbf353f80,0xbf350000,0xbf353f80,
0xbf803f80,0x0,0xbf803f80,0x0,0xbf803f80,0x0,0xbf803f80,0x0,0xbf803f80,0x0,0xbf803f80,0x0,0xbf803f80,0x0,0xbf803f80,0x0,
0xbf353f80,0xbf350000,0xbf353f80,0xbf350000,0x3f350000,0xbf353f80,0x3f350000,0xbf353f80,0x3f35bf80,0x3f350000,0x3f35bf80,0x3f350000,0xbf350000,0x3f35bf80,0xbf350000,0x3f35bf80,
0x3f80,0xbf800000,0x3f80,0xbf800000,0xbf80,0x3f800000,0xbf80,0x3f800000,0x3f80,0xbf800000,0x3f80,0xbf800000,0xbf80,0x3f800000,0xbf80,0x3f800000,
0x3f353f80,0xbf350000,0x3f353f80,0xbf350000,0xbf350000,0xbf35bf80,0xbf350000,0xbf35bf80,0xbf35bf80,0x3f350000,0xbf35bf80,0x3f350000,0x3f350000,0x3f353f80,0x3f350000,0x3f353f80,
0x3f353f80,0xbf350000,0x3f353f80,0xbf350000,0xbf350000,0xbf35bf80,0xbf350000,0xbf35bf80,0xbf35bf80,0x3f350000,0xbf35bf80,0x3f350000,0x3f350000,0x3f353f80,0x3f350000,0x3f353f80,
0x3f80,0xbf800000,0x3f80,0xbf800000,0xbf80,0x3f800000,0xbf80,0x3f800000,0x3f80,0xbf800000,0x3f80,0xbf800000,0xbf80,0x3f800000,0xbf80,0x3f800000,
0xbf353f80,0xbf350000,0xbf353f80,0xbf350000,0x3f350000,0xbf353f80,0x3f350000,0xbf353f80,0x3f35bf80,0x3f350000,0x3f35bf80,0x3f350000,0xbf350000,0x3f35bf80,0xbf350000,0x3f35bf80,
0xbf803f80,0x0,0xbf803f80,0x0,0xbf803f80,0x0,0xbf803f80,0x0,0xbf803f80,0x0,0xbf803f80,0x0,0xbf803f80,0x0,0xbf803f80,0x0,
0xbf353f80,0x3f350000,0xbf353f80,0x3f350000,0x3f350000,0x3f35bf80,0x3f350000,0x3f35bf80,0x3f35bf80,0xbf350000,0x3f35bf80,0xbf350000,0xbf350000,0xbf353f80,0xbf350000,0xbf353f80,
0x3f80,0x3f800000,0x3f80,0x3f800000,0xbf80,0xbf800000,0xbf80,0xbf800000,0x3f80,0x3f800000,0x3f80,0x3f800000,0xbf80,0xbf800000,0xbf80,0xbf800000,
0x3f353f80,0x3f350000,0x3f353f80,0x3f350000,0xbf350000,0x3f353f80,0xbf350000,0x3f353f80,0xbf35bf80,0xbf350000,0xbf35bf80,0xbf350000,0x3f350000,0xbf35bf80,0x3f350000,0xbf35bf80,
0x3f803f80,0x0,0x3f803f80,0x0,0x3f803f80,0x0,0x3f803f80,0x0,0x3f803f80,0x0,0x3f803f80,0x0,0x3f803f80,0x0,0x3f803f80,0x0,
0x3f803f80,0x0,0x0,0x3f803f80,0x3f803f80,0x0,0x0,0x3f803f80,0x3f803f80,0x0,0x0,0x3f803f80,0x3f803f80,0x0,0x0,0x3f803f80,
0x3f0e3f7b,0x3f553e48,0xbf55be48,0x3f0e3f7b,0xbf55be48,0x3f0e3f7b,0xbf0ebf7b,0xbf55be48,0xbf0ebf7b,0xbf55be48,0x3f553e48,0xbf0ebf7b,0x3f553e48,0xbf0ebf7b,0x3f0e3f7b,0x3f553e48,
0xbec43f6d,0x3f6d3ec4,0xbf6dbec4,0xbec43f6d,0x3ec4bf6d,0xbf6dbec4,0x3f6d3ec4,0x3ec4bf6d,0xbec43f6d,0x3f6d3ec4,0xbf6dbec4,0xbec43f6d,0x3ec4bf6d,0xbf6dbec4,0x3f6d3ec4,0x3ec4bf6d,
0xbf7b3f55,0x3e483f0e,0xbe48bf0e,0xbf7b3f55,0x3e483f0e,0x3f7bbf55,0xbf7b3f55,0x3e483f0e,0x3f7bbf55,0xbe48bf0e,0x3e483f0e,0x3f7bbf55,0xbe48bf0e,0xbf7b3f55,0x3f7bbf55,0xbe48bf0e,
0xbf353f35,0xbf353f35,0x3f35bf35,0xbf353f35,0xbf353f35,0xbf353f35,0x3f35bf35,0xbf353f35,0xbf353f35,0xbf353f35,0x3f35bf35,0xbf353f35,0xbf353f35,0xbf353f35,0x3f35bf35,0xbf353f35,
0x3e483f0e,0xbf7b3f55,0x3f7bbf55,0x3e483f0e,0x3f7bbf55,0x3e483f0e,0xbe48bf0e,0x3f7bbf55,0xbe48bf0e,0x3f7bbf55,0xbf7b3f55,0xbe48bf0e,0xbf7b3f55,0xbe48bf0e,0x3e483f0e,0xbf7b3f55,
0x3f6d3ec4,0xbec43f6d,0x3ec4bf6d,0x3f6d3ec4,0xbf6dbec4,0x3ec4bf6d,0xbec43f6d,0xbf6dbec4,0x3f6d3ec4,0xbec43f6d,0x3ec4bf6d,0x3f6d3ec4,0xbf6dbec4,0x3ec4bf6d,0xbec43f6d,0xbf6dbec4,
0x3f553e48,0x3f0e3f7b,0xbf0ebf7b,0x3f553e48,0x3f0e3f7b,0xbf55be48,0x3f553e48,0x3f0e3f7b,0xbf55be48,0xbf0ebf7b,0x3f0e3f7b,0xbf55be48,0xbf0ebf7b,0x3f553e48,0xbf55be48,0xbf0ebf7b,
0x3f0e3f7b,0xbf55be48,0xbf55be48,0xbf0ebf7b,0xbf55be48,0xbf0ebf7b,0xbf0ebf7b,0x3f553e48,0xbf0ebf7b,0x3f553e48,0x3f553e48,0x3f0e3f7b,0x3f553e48,0x3f0e3f7b,0x3f0e3f7b,0xbf55be48,
0xbec43f6d,0xbf6dbec4,0xbf6dbec4,0x3ec4bf6d,0x3ec4bf6d,0x3f6d3ec4,0x3f6d3ec4,0xbec43f6d,0xbec43f6d,0xbf6dbec4,0xbf6dbec4,0x3ec4bf6d,0x3ec4bf6d,0x3f6d3ec4,0x3f6d3ec4,0xbec43f6d,
0xbf7b3f55,0xbe48bf0e,0xbe48bf0e,0x3f7bbf55,0x3e483f0e,0xbf7b3f55,0xbf7b3f55,0xbe48bf0e,0x3f7bbf55,0x3e483f0e,0x3e483f0e,0xbf7b3f55,0xbe48bf0e,0x3f7bbf55,0x3f7bbf55,0x3e483f0e,
0xbf353f35,0x3f35bf35,0x3f35bf35,0x3f35bf35,0xbf353f35,0x3f35bf35,0x3f35bf35,0x3f35bf35,0xbf353f35,0x3f35bf35,0x3f35bf35,0x3f35bf35,0xbf353f35,0x3f35bf35,0x3f35bf35,0x3f35bf35,
0x3e483f0e,0x3f7bbf55,0x3f7bbf55,0xbe48bf0e,0x3f7bbf55,0xbe48bf0e,0xbe48bf0e,0xbf7b3f55,0xbe48bf0e,0xbf7b3f55,0xbf7b3f55,0x3e483f0e,0xbf7b3f55,0x3e483f0e,0x3e483f0e,0x3f7bbf55,
0x3f6d3ec4,0x3ec4bf6d,0x3ec4bf6d,0xbf6dbec4,0xbf6dbec4,0xbec43f6d,0xbec43f6d,0x3f6d3ec4,0x3f6d3ec4,0x3ec4bf6d,0x3ec4bf6d,0xbf6dbec4,0xbf6dbec4,0xbec43f6d,0xbec43f6d,0x3f6d3ec4,
0x3f553e48,0xbf0ebf7b,0xbf0ebf7b,0xbf55be48,0x3f0e3f7b,0x3f553e48,0x3f553e48,0xbf0ebf7b,0xbf55be48,0x3f0e3f7b,0x3f0e3f7b,0x3f553e48,0xbf0ebf7b,0xbf55be48,0xbf55be48,0x3f0e3f7b,
0x0,0xbf80bf80,0xbf80bf80,0x0,0x0,0xbf80bf80,0xbf80bf80,0x0,0x0,0xbf80bf80,0xbf80bf80,0x0,0x0,0xbf80bf80,0xbf80bf80,0x0,
0x3f803f80,0x0,0xbf80bf80,0x0,0x3f803f80,0x0,0xbf80bf80,0x0,0x3f803f80,0x0,0xbf80bf80,0x0,0x3f803f80,0x0,0xbf80bf80,0x0,
0x3ec43f6d,0x3f6d3ec4,0xbec4bf6d,0xbf6dbec4,0xbf6dbec4,0x3ec43f6d,0x3f6d3ec4,0xbec4bf6d,0xbec4bf6d,0xbf6dbec4,0x3ec43f6d,0x3f6d3ec4,0x3f6d3ec4,0xbec4bf6d,0xbf6dbec4,0x3ec43f6d,
0xbf353f35,0x3f353f35,0x3f35bf35,0xbf35bf35,0x3f35bf35,0xbf35bf35,0xbf353f35,0x3f353f35,0xbf353f35,0x3f353f35,0x3f35bf35,0xbf35bf35,0x3f35bf35,0xbf35bf35,0xbf353f35,0x3f353f35,
0xbf6d3ec4,0xbec43f6d,0x3f6dbec4,0x3ec4bf6d,0xbec43f6d,0x3f6dbec4,0x3ec4bf6d,0xbf6d3ec4,0x3f6dbec4,0x3ec4bf6d,0xbf6d3ec4,0xbec43f6d,0x3ec4bf6d,0xbf6d3ec4,0xbec43f6d,0x3f6dbec4,
0x0,0xbf803f80,0x0,0x3f80bf80,0x0,0xbf803f80,0x0,0x3f80bf80,0x0,0xbf803f80,0x0,0x3f80bf80,0x0,0xbf803f80,0x0,0x3f80bf80,
0x3f6dbec4,0xbec43f6d,0xbf6d3ec4,0x3ec4bf6d,0x3ec4bf6d,0x3f6dbec4,0xbec43f6d,0xbf6d3ec4,0xbf6d3ec4,0x3ec4bf6d,0x3f6dbec4,0xbec43f6d,0xbec43f6d,0xbf6d3ec4,0x3ec4bf6d,0x3f6dbec4,
0x3f35bf35,0x3f353f35,0xbf353f35,0xbf35bf35,0xbf353f35,0xbf35bf35,0x3f35bf35,0x3f353f35,0x3f35bf35,0x3f353f35,0xbf353f35,0xbf35bf35,0xbf353f35,0xbf35bf35,0x3f35bf35,0x3f353f35,
0xbec4bf6d,0x3f6d3ec4,0x3ec43f6d,0xbf6dbec4,0x3f6d3ec4,0x3ec43f6d,0xbf6dbec4,0xbec4bf6d,0x3ec43f6d,0xbf6dbec4,0xbec4bf6d,0x3f6d3ec4,0xbf6dbec4,0xbec4bf6d,0x3f6d3ec4,0x3ec43f6d,
0x3ec43f6d,0xbf6dbec4,0xbec4bf6d,0x3f6d3ec4,0xbf6dbec4,0xbec4bf6d,0x3f6d3ec4,0x3ec43f6d,0xbec4bf6d,0x3f6d3ec4,0x3ec43f6d,0xbf6dbec4,0x3f6d3ec4,0x3ec43f6d,0xbf6dbec4,0xbec4bf6d,
0xbf353f35,0xbf35bf35,0x3f35bf35,0x3f353f35,0x3f35bf35,0x3f353f35,0xbf353f35,0xbf35bf35,0xbf353f35,0xbf35bf35,0x3f35bf35,0x3f353f35,0x3f35bf35,0x3f353f35,0xbf353f35,0xbf35bf35,
0xbf6d3ec4,0x3ec4bf6d,0x3f6dbec4,0xbec43f6d,0xbec43f6d,0xbf6d3ec4,0x3ec4bf6d,0x3f6dbec4,0x3f6dbec4,0xbec43f6d,0xbf6d3ec4,0x3ec4bf6d,0x3ec4bf6d,0x3f6dbec4,0xbec43f6d,0xbf6d3ec4,
0x0,0x3f80bf80,0x0,0xbf803f80,0x0,0x3f80bf80,0x0,0xbf803f80,0x0,0x3f80bf80,0x0,0xbf803f80,0x0,0x3f80bf80,0x0,0xbf803f80,
0x3f6dbec4,0x3ec4bf6d,0xbf6d3ec4,0xbec43f6d,0x3ec4bf6d,0xbf6d3ec4,0xbec43f6d,0x3f6dbec4,0xbf6d3ec4,0xbec43f6d,0x3f6dbec4,0x3ec4bf6d,0xbec43f6d,0x3f6dbec4,0x3ec4bf6d,0xbf6d3ec4,
0x3f35bf35,0xbf35bf35,0xbf353f35,0x3f353f35,0xbf353f35,0x3f353f35,0x3f35bf35,0xbf35bf35,0x3f35bf35,0xbf35bf35,0xbf353f35,0x3f353f35,0xbf353f35,0x3f353f35,0x3f35bf35,0xbf35bf35,
0xbec4bf6d,0xbf6dbec4,0x3ec43f6d,0x3f6d3ec4,0x3f6d3ec4,0xbec4bf6d,0xbf6dbec4,0x3ec43f6d,0x3ec43f6d,0x3f6d3ec4,0xbec4bf6d,0xbf6dbec4,0xbf6dbec4,0x3ec43f6d,0x3f6d3ec4,0xbec4bf6d,
0xbf80bf80,0x0,0x3f803f80,0x0,0xbf80bf80,0x0,0x3f803f80,0x0,0xbf80bf80,0x0,0x3f803f80,0x0,0xbf80bf80,0x0,0x3f803f80,0x0,
0x3f803f80,0x0,0x0,0xbf80bf80,0x3f803f80,0x0,0x0,0xbf80bf80,0x3f803f80,0x0,0x0,0xbf80bf80,0x3f803f80,0x0,0x0,0xbf80bf80,
0x3e483f55,0x3f7b3f0e,0x3f7b3f0e,0xbe48bf55,0xbf7bbf0e,0x3e483f55,0x3e483f55,0x3f7b3f0e,0xbe48bf55,0xbf7bbf0e,0xbf7bbf0e,0x3e483f55,0x3f7b3f0e,0xbe48bf55,0xbe48bf55,0xbf7bbf0e,
0xbf6d3ec4,0x3ec43f6d,0x3ec43f6d,0x3f6dbec4,0x3f6dbec4,0xbec4bf6d,0xbec4bf6d,0xbf6d3ec4,0xbf6d3ec4,0x3ec43f6d,0x3ec43f6d,0x3f6dbec4,0x3f6dbec4,0xbec4bf6d,0xbec4bf6d,0xbf6d3ec4,
0xbf0ebe48,0xbf553f7b,0xbf553f7b,0x3f0e3e48,0xbf553f7b,0x3f0e3e48,0x3f0e3e48,0x3f55bf7b,0x3f0e3e48,0x3f55bf7b,0x3f55bf7b,0xbf0ebe48,0x3f55bf7b,0xbf0ebe48,0xbf0ebe48,0xbf553f7b,
0x3f35bf35,0xbf353f35,0xbf353f35,0xbf353f35,0x3f35bf35,0xbf353f35,0xbf353f35,0xbf353f35,0x3f35bf35,0xbf353f35,0xbf353f35,0xbf353f35,0x3f35bf35,0xbf353f35,0xbf353f35,0xbf353f35,
0x3f55bf7b,0x3f0e3e48,0x3f0e3e48,0xbf553f7b,0xbf0ebe48,0x3f55bf7b,0x3f55bf7b,0x3f0e3e48,0xbf553f7b,0xbf0ebe48,0xbf0ebe48,0x3f55bf7b,0x3f0e3e48,0xbf553f7b,0xbf553f7b,0xbf0ebe48,
0xbec4bf6d,0x3f6dbec4,0x3f6dbec4,0x3ec43f6d,0x3ec43f6d,0xbf6d3ec4,0xbf6d3ec4,0xbec4bf6d,0xbec4bf6d,0x3f6dbec4,0x3f6dbec4,0x3ec43f6d,0x3ec43f6d,0xbf6d3ec4,0xbf6d3ec4,0xbec4bf6d,
0xbf7bbf0e,0xbe48bf55,0xbe48bf55,0x3f7b3f0e,0xbe48bf55,0x3f7b3f0e,0x3f7b3f0e,0x3e483f55,0x3f7b3f0e,0x3e483f55,0x3e483f55,0xbf7bbf0e,0x3e483f55,0xbf7bbf0e,0xbf7bbf0e,0xbe48bf55,
0x3e483f55,0xbf7bbf0e,0x3f7b3f0e,0x3e483f55,0xbf7bbf0e,0xbe48bf55,0x3e483f55,0xbf7bbf0e,0xbe48bf55,0x3f7b3f0e,0xbf7bbf0e,0xbe48bf55,0x3f7b3f0e,0x3e483f55,0xbe48bf55,0x3f7b3f0e,
0xbf6d3ec4,0xbec4bf6d,0x3ec43f6d,0xbf6d3ec4,0x3f6dbec4,0x3ec43f6d,0xbec4bf6d,0x3f6dbec4,0xbf6d3ec4,0xbec4bf6d,0x3ec43f6d,0xbf6d3ec4,0x3f6dbec4,0x3ec43f6d,0xbec4bf6d,0x3f6dbec4,
0xbf0ebe48,0x3f55bf7b,0xbf553f7b,0xbf0ebe48,0xbf553f7b,0xbf0ebe48,0x3f0e3e48,0xbf553f7b,0x3f0e3e48,0xbf553f7b,0x3f55bf7b,0x3f0e3e48,0x3f55bf7b,0x3f0e3e48,0xbf0ebe48,0x3f55bf7b,
0x3f35bf35,0x3f35bf35,0xbf353f35,0x3f35bf35,0x3f35bf35,0x3f35bf35,0xbf353f35,0x3f35bf35,0x3f35bf35,0x3f35bf35,0xbf353f35,0x3f35bf35,0x3f35bf35,0x3f35bf35,0xbf353f35,0x3f35bf35,
0x3f55bf7b,0xbf0ebe48,0x3f0e3e48,0x3f55bf7b,0xbf0ebe48,0xbf553f7b,0x3f55bf7b,0xbf0ebe48,0xbf553f7b,0x3f0e3e48,0xbf0ebe48,0xbf553f7b,0x3f0e3e48,0x3f55bf7b,0xbf553f7b,0x3f0e3e48,
0xbec4bf6d,0xbf6d3ec4,0x3f6dbec4,0xbec4bf6d,0x3ec43f6d,0x3f6dbec4,0xbf6d3ec4,0x3ec43f6d,0xbec4bf6d,0xbf6d3ec4,0x3f6dbec4,0xbec4bf6d,0x3ec43f6d,0x3f6dbec4,0xbf6d3ec4,0x3ec43f6d,
0xbf7bbf0e,0x3e483f55,0xbe48bf55,0xbf7bbf0e,0xbe48bf55,0xbf7bbf0e,0x3f7b3f0e,0xbe48bf55,0x3f7b3f0e,0xbe48bf55,0x3e483f55,0x3f7b3f0e,0x3e483f55,0x3f7b3f0e,0xbf7bbf0e,0x3e483f55,
0x0,0x3f803f80,0xbf80bf80,0x0,0x0,0x3f803f80,0xbf80bf80,0x0,0x0,0x3f803f80,0xbf80bf80,0x0,0x0,0x3f803f80,0xbf80bf80,0x0,
0x3f6d3f80,0x3f623f7f,0xbec40000,0xbef1bdc9,0x3ec43f35,0x3e953f22,0xbf6dbf35,0xbf75bf46,0xbec40000,0xbef1bdc9,0xbf6dbf80,0xbf62bf7f,0xbf6dbf35,0xbf75bf46,0xbec4bf35,0xbe95bf22,
0x3ec43f80,0x3dc93f75,0xbf6d0000,0xbf7fbe95,0xbf6dbf35,0xbf46bf62,0x3ec4bf35,0x3f22bef1,0x3f6d0000,0x3f7f3e95,0x3ec43f80,0x3dc93f75,0xbec43f35,0xbf223ef1,0xbf6dbf35,0xbf46bf62,
0xbec43f80,0xbf463f62,0xbf6d0000,0xbf22bef1,0x3f6dbf35,0x3f7fbe95,0x3ec43f35,0xbdc93f75,0xbf6d0000,0xbf22bef1,0x3ec4bf80,0x3f46bf62,0x3ec43f35,0xbdc93f75,0xbf6d3f35,0xbf7f3e95,
0xbf6d3f80,0xbf753f46,0xbec40000,0x3e95bf22,0xbec43f35,0xbf623f7f,0xbf6d3f35,0xbef13dc9,0x3ec40000,0xbe953f22,0xbf6d3f80,0xbf753f46,0x3f6dbf35,0x3ef1bdc9,0xbec43f35,0xbf623f7f,
0xbf6d3f80,0xbe953f22,0x3ec40000,0x3f75bf46,0xbec43f35,0x3ef1bdc9,0x3f6dbf35,0x3f62bf7f,0x3ec40000,0x3f75bf46,0x3f6dbf80,0x3e95bf22,0x3f6dbf35,0x3f62bf7f,0x3ec4bf35,0xbef13dc9,
0xbec43f80,0x3f223ef1,0x3f6d0000,0x3f46bf62,0x3f6dbf35,0x3dc9bf75,0xbec4bf35,0xbf7f3e95,0xbf6d0000,0xbf463f62,0xbec43f80,0x3f223ef1,0x3ec43f35,0x3f7fbe95,0x3f6dbf35,0x3dc9bf75,
0x3ec43f80,0x3f7f3e95,0x3f6d0000,0xbdc9bf75,0xbf6dbf35,0xbf223ef1,0xbec43f35,0x3f463f62,0x3f6d0000,0xbdc9bf75,0xbec4bf80,0xbf7fbe95,0xbec43f35,0x3f463f62,0x3f6d3f35,0x3f22bef1,
0x3f6d3f80,0x3ef13dc9,0x3ec40000,0xbf62bf7f,0x3ec43f35,0x3f753f46,0x3f6d3f35,0xbe95bf22,0xbec40000,0x3f623f7f,0x3f6d3f80,0x3ef13dc9,0xbf6dbf35,0x3e953f22,0x3ec43f35,0x3f753f46,
0x3f6d3f80,0xbef1bdc9,0xbec40000,0xbf62bf7f,0x3ec43f35,0xbf75bf46,0xbf6dbf35,0xbe95bf22,0xbec40000,0xbf62bf7f,0xbf6dbf80,0x3ef13dc9,0xbf6dbf35,0xbe95bf22,0xbec4bf35,0x3f753f46,
0x3ec43f80,0xbf7fbe95,0xbf6d0000,0xbdc9bf75,0xbf6dbf35,0x3f22bef1,0x3ec4bf35,0x3f463f62,0x3f6d0000,0x3dc93f75,0x3ec43f80,0xbf7fbe95,0xbec43f35,0xbf46bf62,0xbf6dbf35,0x3f22bef1,
0xbec43f80,0xbf22bef1,0xbf6d0000,0x3f46bf62,0x3f6dbf35,0xbdc93f75,0x3ec43f35,0xbf7f3e95,0xbf6d0000,0x3f46bf62,0x3ec4bf80,0x3f223ef1,0x3ec43f35,0xbf7f3e95,0xbf6d3f35,0x3dc9bf75,
0xbf6d3f80,0x3e95bf22,0xbec40000,0x3f75bf46,0xbec43f35,0xbef13dc9,0xbf6d3f35,0x3f62bf7f,0x3ec40000,0xbf753f46,0xbf6d3f80,0x3e95bf22,0x3f6dbf35,0xbf623f7f,0xbec43f35,0xbef13dc9,
0xbf6d3f80,0x3f75bf46,0x3ec40000,0x3e95bf22,0xbec43f35,0x3f62bf7f,0x3f6dbf35,0xbef13dc9,0x3ec40000,0x3e95bf22,0x3f6dbf80,0xbf753f46,0x3f6dbf35,0xbef13dc9,0x3ec4bf35,0xbf623f7f,
0xbec43f80,0x3f46bf62,0x3f6d0000,0xbf22bef1,0x3f6dbf35,0xbf7f3e95,0xbec4bf35,0xbdc93f75,0xbf6d0000,0x3f223ef1,0xbec43f80,0x3f46bf62,0x3ec43f35,0x3dc9bf75,0x3f6dbf35,0xbf7f3e95,
0x3ec43f80,0xbdc9bf75,0x3f6d0000,0xbf7fbe95,0xbf6dbf35,0x3f463f62,0xbec43f35,0x3f22bef1,0x3f6d0000,0xbf7fbe95,0xbec4bf80,0x3dc93f75,0xbec43f35,0x3f22bef1,0x3f6d3f35,0xbf46bf62,
0x3f6d3f80,0xbf62bf7f,0x3ec40000,0xbef1bdc9,0x3ec43f35,0xbe95bf22,0x3f6d3f35,0xbf75bf46,0xbec40000,0x3ef13dc9,0x3f6d3f80,0xbf62bf7f,0xbf6dbf35,0x3f753f46,0x3ec43f35,0xbe95bf22,
0x3f553f7b,0x3f463f75,0xbf0ebe48,0xbf22be95,0x3e483f0e,0x3dc93ef1,0xbf7bbf55,0xbf7fbf62,0xbf0ebe48,0xbf22be95,0xbf55bf7b,0xbf46bf75,0xbf7bbf55,0xbf7fbf62,0xbe48bf0e,0xbdc9bef1,
0xbe483f55,0xbef13f22,0xbf7bbf0e,0xbf62bf46,0xbf0ebf7b,0xbe95bf7f,0x3f55be48,0x3f753dc9,0x3f7b3f0e,0x3f623f46,0xbe483f55,0xbef13f22,0xbf553e48,0xbf75bdc9,0xbf0ebf7b,0xbe95bf7f,
0xbf7b3f0e,0xbf753dc9,0xbe48bf55,0x3e95bf7f,0x3f553e48,0x3ef13f22,0xbf0e3f7b,0xbf623f46,0xbe48bf55,0x3e95bf7f,0x3f7bbf0e,0x3f75bdc9,0xbf0e3f7b,0xbf623f46,0xbf55be48,0xbef1bf22,
0xbf0e3e48,0x3dc9bef1,0x3f55bf7b,0x3f7fbf62,0xbf7b3f55,0xbf223e95,0x3e48bf0e,0x3f46bf75,0xbf553f7b,0xbf7f3f62,0xbf0e3e48,0x3dc9bef1,0xbe483f0e,0xbf463f75,0xbf7b3f55,0xbf223e95,
0x3f0ebe48,0x3f7fbf62,0x3f55bf7b,0x3dc9bef1,0x3f7bbf55,0x3f46bf75,0x3e48bf0e,0xbf223e95,0x3f55bf7b,0x3dc9bef1,0xbf0e3e48,0xbf7f3f62,0x3e48bf0e,0xbf223e95,0xbf7b3f55,0xbf463f75,
0x3f7bbf0e,0x3e95bf7f,0xbe48bf55,0xbf753dc9,0xbf55be48,0xbf623f46,0xbf0e3f7b,0x3ef13f22,0x3e483f55,0x3f75bdc9,0x3f7bbf0e,0x3e95bf7f,0x3f0ebf7b,0xbef1bf22,0xbf55be48,0xbf623f46,
0x3e48bf55,0xbf62bf46,0xbf7bbf0e,0xbef13f22,0x3f0e3f7b,0x3f753dc9,0x3f55be48,0xbe95bf7f,0xbf7bbf0e,0xbef13f22,0xbe483f55,0x3f623f46,0x3f55be48,0xbe95bf7f,0xbf0ebf7b,0xbf75bdc9,
0xbf55bf7b,0xbf22be95,0xbf0ebe48,0x3f463f75,0xbe48bf0e,0xbf7fbf62,0xbf7bbf55,0x3dc93ef1,0x3f0e3e48,0xbf46bf75,0xbf55bf7b,0xbf22be95,0x3f7b3f55,0xbdc9bef1,0xbe48bf0e,0xbf7fbf62,
0xbf55bf7b,0x3f223e95,0x3f0e3e48,0x3f463f75,0xbe48bf0e,0x3f7f3f62,0x3f7b3f55,0x3dc93ef1,0x3f0e3e48,0x3f463f75,0x3f553f7b,0xbf22be95,0x3f7b3f55,0x3dc93ef1,0x3e483f0e,0xbf7fbf62,
0x3e48bf55,0x3f623f46,0x3f7b3f0e,0xbef13f22,0x3f0e3f7b,0xbf75bdc9,0xbf553e48,0xbe95bf7f,0xbf7bbf0e,0x3ef1bf22,0x3e48bf55,0x3f623f46,0x3f55be48,0x3e953f7f,0x3f0e3f7b,0xbf75bdc9,
0x3f7bbf0e,0xbe953f7f,0x3e483f55,0xbf753dc9,0xbf55be48,0x3f62bf46,0x3f0ebf7b,0x3ef13f22,0x3e483f55,0xbf753dc9,0xbf7b3f0e,0x3e95bf7f,0x3f0ebf7b,0x3ef13f22,0x3f553e48,0xbf623f46,
0x3f0ebe48,0xbf7f3f62,0xbf553f7b,0x3dc9bef1,0x3f7bbf55,0xbf463f75,0xbe483f0e,0xbf223e95,0x3f55bf7b,0xbdc93ef1,0x3f0ebe48,0xbf7f3f62,0x3e48bf0e,0x3f22be95,0x3f7bbf55,0xbf463f75,
0xbf0e3e48,0xbdc93ef1,0xbf553f7b,0x3f7fbf62,0xbf7b3f55,0x3f22be95,0xbe483f0e,0x3f46bf75,0xbf553f7b,0x3f7fbf62,0x3f0ebe48,0x3dc9bef1,0xbe483f0e,0x3f46bf75,0x3f7bbf55,0xbf223e95,
0xbf7b3f0e,0x3f75bdc9,0x3e483f55,0x3e95bf7f,0x3f553e48,0xbef1bf22,0x3f0ebf7b,0xbf623f46,0xbe48bf55,0xbe953f7f,0xbf7b3f0e,0x3f75bdc9,0xbf0e3f7b,0x3f62bf46,0x3f553e48,0xbef1bf22,
0xbe483f55,0x3ef1bf22,0x3f7b3f0e,0xbf62bf46,0xbf0ebf7b,0x3e953f7f,0xbf553e48,0x3f753dc9,0x3f7b3f0e,0xbf62bf46,0x3e48bf55,0xbef13f22,0xbf553e48,0x3f753dc9,0x3f0e3f7b,0xbe95bf7f,
0x3f553f7b,0xbf46bf75,0x3f0e3e48,0xbf22be95,0x3e483f0e,0xbdc9bef1,0x3f7b3f55,0xbf7fbf62,0xbf0ebe48,0x3f223e95,0x3f553f7b,0xbf46bf75,0xbf7bbf55,0x3f7f3f62,0x3e483f0e,0xbdc9bef1,
0x3f80,0x3f80,0x3f80,0x3f80,0x3f80,0xbf80,0x3f80,0xbf80,0x3f80,0x3f80,0x3f80,0x3f80,0x3f80,0xbf80,0x3f80,0xbf80,
0x3f80,0x3f80,0x3f800000,0x3f800000,0x3ec43f6d,0xbec4bf6d,0x3f6dbec4,0xbf6d3ec4,0x3f353f35,0x3f353f35,0x3f35bf35,0x3f35bf35,0x3f6d3ec4,0xbf6dbec4,0x3ec4bf6d,0xbec43f6d,
0x3f80,0x3f80,0xbf80,0xbf80,0x3f353f35,0xbf35bf35,0xbf35bf35,0x3f353f35,0x3f800000,0x3f800000,0xbf800000,0xbf800000,0x3f35bf35,0xbf353f35,0xbf353f35,0x3f35bf35,
0x3f80,0x3f80,0xbf800000,0xbf800000,0x3f6d3ec4,0xbf6dbec4,0xbec43f6d,0x3ec4bf6d,0x3f35bf35,0x3f35bf35,0x3f353f35,0x3f353f35,0xbec4bf6d,0x3ec43f6d,0x3f6dbec4,0xbf6d3ec4,
0x3f80,0x3f80,0x3f80,0x3f80,0x3f800000,0xbf800000,0x3f800000,0xbf800000,0xbf80,0xbf80,0xbf80,0xbf80,0xbf800000,0x3f800000,0xbf800000,0x3f800000,
0x3f80,0x3f80,0x3f800000,0x3f800000,0x3f6dbec4,0xbf6d3ec4,0xbec4bf6d,0x3ec43f6d,0xbf35bf35,0xbf35bf35,0xbf353f35,0xbf353f35,0xbec43f6d,0x3ec4bf6d,0x3f6d3ec4,0xbf6dbec4,
0x3f80,0x3f80,0xbf80,0xbf80,0x3f35bf35,0xbf353f35,0xbf353f35,0x3f35bf35,0xbf800000,0xbf800000,0x3f800000,0x3f800000,0x3f353f35,0xbf35bf35,0xbf35bf35,0x3f353f35,
0x3f80,0x3f80,0xbf800000,0xbf800000,0x3ec4bf6d,0xbec43f6d,0x3f6d3ec4,0xbf6dbec4,0xbf353f35,0xbf353f35,0xbf35bf35,0xbf35bf35,0x3f6dbec4,0xbf6d3ec4,0x3ec43f6d,0xbec4bf6d,
0x3f800000,0x3f800000,0x3f800000,0x3f800000,0x3f800000,0xbf800000,0x3f800000,0xbf800000,0x3f800000,0x3f800000,0x3f800000,0x3f800000,0x3f800000,0xbf800000,0x3f800000,0xbf800000,
0x3f800000,0x3f800000,0xbf80,0xbf80,0x3f6dbec4,0xbf6d3ec4,0xbec4bf6d,0x3ec43f6d,0x3f35bf35,0x3f35bf35,0xbf35bf35,0xbf35bf35,0x3ec4bf6d,0xbec43f6d,0xbf6dbec4,0x3f6d3ec4,
0x3f800000,0x3f800000,0xbf800000,0xbf800000,0x3f35bf35,0xbf353f35,0xbf353f35,0x3f35bf35,0xbf80,0xbf80,0x3f80,0x3f80,0xbf35bf35,0x3f353f35,0x3f353f35,0xbf35bf35,
0x3f800000,0x3f800000,0x3f80,0x3f80,0x3ec4bf6d,0xbec43f6d,0x3f6d3ec4,0xbf6dbec4,0xbf35bf35,0xbf35bf35,0x3f35bf35,0x3f35bf35,0xbf6d3ec4,0x3f6dbec4,0xbec4bf6d,0x3ec43f6d,
0x3f800000,0x3f800000,0x3f800000,0x3f800000,0xbf80,0x3f80,0xbf80,0x3f80,0xbf800000,0xbf800000,0xbf800000,0xbf800000,0x3f80,0xbf80,0x3f80,0xbf80,
0x3f800000,0x3f800000,0xbf80,0xbf80,0xbec4bf6d,0x3ec43f6d,0xbf6d3ec4,0x3f6dbec4,0xbf353f35,0xbf353f35,0x3f353f35,0x3f353f35,0x3f6d3ec4,0xbf6dbec4,0x3ec4bf6d,0xbec43f6d,
0x3f800000,0x3f800000,0xbf800000,0xbf800000,0xbf35bf35,0x3f353f35,0x3f353f35,0xbf35bf35,0x3f80,0x3f80,0xbf80,0xbf80,0x3f35bf35,0xbf353f35,0xbf353f35,0x3f35bf35,
0x3f800000,0x3f800000,0x3f80,0x3f80,0xbf6dbec4,0x3f6d3ec4,0x3ec4bf6d,0xbec43f6d,0x3f353f35,0x3f353f35,0xbf353f35,0xbf353f35,0xbec4bf6d,0x3ec43f6d,0x3f6dbec4,0xbf6d3ec4,
0x3f80,0x3f80,0x3f80,0x3f80,0x3f80,0xbf80,0x3f80,0xbf80,0x3f80,0x3f80,0x3f80,0x3f80,0x3f80,0xbf80,0x3f80,0xbf80,
0xbf80,0xbf80,0xbf800000,0xbf800000,0xbec4bf6d,0x3ec43f6d,0xbf6d3ec4,0x3f6dbec4,0xbf35bf35,0xbf35bf35,0xbf353f35,0xbf353f35,0xbf6dbec4,0x3f6d3ec4,0xbec43f6d,0x3ec4bf6d,
0x3f80,0x3f80,0xbf80,0xbf80,0x3f353f35,0xbf35bf35,0xbf35bf35,0x3f353f35,0x3f800000,0x3f800000,0xbf800000,0xbf800000,0x3f35bf35,0xbf353f35,0xbf353f35,0x3f35bf35,
0xbf80,0xbf80,0x3f800000,0x3f800000,0xbf6dbec4,0x3f6d3ec4,0x3ec4bf6d,0xbec43f6d,0xbf353f35,0xbf353f35,0xbf35bf35,0xbf35bf35,0x3ec43f6d,0xbec4bf6d,0xbf6d3ec4,0x3f6dbec4,
0x3f80,0x3f80,0x3f80,0x3f80,0x3f800000,0xbf800000,0x3f800000,0xbf800000,0xbf80,0xbf80,0xbf80,0xbf80,0xbf800000,0x3f800000,0xbf800000,0x3f800000,
0xbf80,0xbf80,0xbf800000,0xbf800000,0xbf6d3ec4,0x3f6dbec4,0x3ec43f6d,0xbec4bf6d,0x3f353f35,0x3f353f35,0x3f35bf35,0x3f35bf35,0x3ec4bf6d,0xbec43f6d,0xbf6dbec4,0x3f6d3ec4,
0x3f80,0x3f80,0xbf80,0xbf80,0x3f35bf35,0xbf353f35,0xbf353f35,0x3f35bf35,0xbf800000,0xbf800000,0x3f800000,0x3f800000,0x3f353f35,0xbf35bf35,0xbf35bf35,0x3f353f35,
0xbf80,0xbf80,0x3f800000,0x3f800000,0xbec43f6d,0x3ec4bf6d,0xbf6dbec4,0x3f6d3ec4,0x3f35bf35,0x3f35bf35,0x3f353f35,0x3f353f35,0xbf6d3ec4,0x3f6dbec4,0xbec4bf6d,0x3ec43f6d,
0x3f800000,0x3f800000,0x3f800000,0x3f800000,0x3f800000,0xbf800000,0x3f800000,0xbf800000,0x3f800000,0x3f800000,0x3f800000,0x3f800000,0x3f800000,0xbf800000,0x3f800000,0xbf800000,
0xbf800000,0xbf800000,0x3f80,0x3f80,0xbf6d3ec4,0x3f6dbec4,0x3ec43f6d,0xbec4bf6d,0xbf353f35,0xbf353f35,0x3f353f35,0x3f353f35,0xbec43f6d,0x3ec4bf6d,0x3f6d3ec4,0xbf6dbec4,
0x3f800000,0x3f800000,0xbf800000,0xbf800000,0x3f35bf35,0xbf353f35,0xbf353f35,0x3f35bf35,0xbf80,0xbf80,0x3f80,0x3f80,0xbf35bf35,0x3f353f35,0x3f353f35,0xbf35bf35,
0xbf800000,0xbf800000,0xbf80,0xbf80,0xbec43f6d,0x3ec4bf6d,0xbf6dbec4,0x3f6d3ec4,0x3f353f35,0x3f353f35,0xbf353f35,0xbf353f35,0x3f6dbec4,0xbf6d3ec4,0x3ec43f6d,0xbec4bf6d,
0x3f800000,0x3f800000,0x3f800000,0x3f800000,0xbf80,0x3f80,0xbf80,0x3f80,0xbf800000,0xbf800000,0xbf800000,0xbf800000,0x3f80,0xbf80,0x3f80,0xbf80,
0xbf800000,0xbf800000,0x3f80,0x3f80,0x3ec43f6d,0xbec4bf6d,0x3f6dbec4,0xbf6d3ec4,0x3f35bf35,0x3f35bf35,0xbf35bf35,0xbf35bf35,0xbf6dbec4,0x3f6d3ec4,0xbec43f6d,0x3ec4bf6d,
0x3f800000,0x3f800000,0xbf800000,0xbf800000,0xbf35bf35,0x3f353f35,0x3f353f35,0xbf35bf35,0x3f80,0x3f80,0xbf80,0xbf80,0x3f35bf35,0xbf353f35,0xbf353f35,0x3f35bf35,
0xbf800000,0xbf800000,0xbf80,0xbf80,0x3f6d3ec4,0xbf6dbec4,0xbec43f6d,0x3ec4bf6d,0xbf35bf35,0xbf35bf35,0x3f35bf35,0x3f35bf35,0x3ec43f6d,0xbec4bf6d,0xbf6d3ec4,0x3f6dbec4,
0x3f800000,0x3f800000,0x3f800000,0x3f6c835e,0x3f800000,0x3f800000,0x3f3504f3,0x3ec3ef15,0x3f800000,0x3f800000,0x0,0xbec3ef15,0x3f800000,0x3f800000,0xbf3504f3,0xbf6c835e,
0x3f800000,0x3f7fb10f,0x3f800000,0x3f676bd8,0x3f7ec46d,0x3f7d3aac,0x3f226799,0x3e78cfcc,0x3f7b14be,0x3f7853f8,0xbe47c5c2,0xbf187fc0,0x3f74fa0b,0x3f710908,0xbf61c598,0xbf7fb10f,
0x3f800000,0x3f7ec46d,0x3f800000,0x3f61c598,0x3f7b14be,0x3f74fa0b,0x3f0e39da,0x3dc8bd36,0x3f6c835e,0x3f61c598,0xbec3ef15,0xbf45e403,0x3f54db31,0x3f45e403,0xbf7b14be,0xbf74fa0b,
0x3f800000,0x3f7d3aac,0x3f800000,0x3f5b941a,0x3f74fa0b,0x3f676bd8,0x3ef15aea,0xbd48fb30,0x3f54db31,0x3f3daef9,0xbf0e39da,0xbf676bd8,0x3f226799,0x3f039c3d,0xbf7ec46d,0xbf4d9f02,
0x3f800000,0x3f7b14be,0x3f800000,0x3f54db31,0x3f6c835e,0x3f54db31,0x3ec3ef15,0xbe47c5c2,0x3f3504f3,0x3f0e39da,0xbf3504f3,0xbf7b14be,0x3ec3ef15,0x3e47c5c2,0xbf6c835e,0xbf0e39da,
0x3f800000,0x3f7853f8,0x3f800000,0x3f4d9f02,0x3f61c598,0x3f3daef9,0x3e94a031,0xbeac7cd4,0x3f0e39da,0x3eac7cd4,0xbf54db31,0xbf7fb10f,0x3dc8bd36,0xbe164083,0xbf45e403,0xbe78cfcc,
0x3f800000,0x3f74fa0b,0x3f800000,0x3f45e403,0x3f54db31,0x3f226799,0x3e47c5c2,0xbef15aea,0x3ec3ef15,0x3dc8bd36,0xbf6c835e,0xbf74fa0b,0xbe47c5c2,0xbef15aea,0xbf0e39da,0x3dc8bd36,
0x3f800000,0x3f710908,0x3f800000,0x3f3daef9,0x3f45e403,0x3f039c3d,0x3dc8bd36,0xbf187fc0,0x3e47c5c2,0xbe164083,0xbf7b14be,0xbf5b941a,0xbef15aea,0xbf3daef9,0xbe94a031,0x3edae880,
0x0,0x0,0x0,0x3ec3ef15,0x0,0x0,0x3f3504f3,0x3f6c835e,0x0,0x0,0x3f800000,0x3f6c835e,0x0,0x0,0x3f3504f3,0x3ec3ef15,
0x0,0x3d48fb30,0x0,0x3edae880,0x3dc8bd36,0x3e164083,0x3f45e403,0x3f7853f8,0x3e47c5c2,0x3e78cfcc,0x3f7b14be,0x3f4d9f02,0x3e94a031,0x3eac7cd4,0x3ef15aea,0x3d48fb30,
0x0,0x3dc8bd36,0x0,0x3ef15aea,0x3e47c5c2,0x3e94a031,0x3f54db31,0x3f7ec46d,0x3ec3ef15,0x3ef15aea,0x3f6c835e,0x3f226799,0x3f0e39da,0x3f226799,0x3e47c5c2,0xbe94a031,
0x0,0x3e164083,0x0,0x3f039c3d,0x3e94a031,0x3edae880,0x3f61c598,0x3f7fb10f,0x3f0e39da,0x3f2beb4a,0x3f54db31,0x3edae880,0x3f45e403,0x3f5b941a,0xbdc8bd36,0xbf187fc0,
0x0,0x3e47c5c2,0x0,0x3f0e39da,0x3ec3ef15,0x3f0e39da,0x3f6c835e,0x3f7b14be,0x3f3504f3,0x3f54db31,0x3f3504f3,0x3e47c5c2,0x3f6c835e,0x3f7b14be,0xbec3ef15,0xbf54db31,
0x0,0x3e78cfcc,0x0,0x3f187fc0,0x3ef15aea,0x3f2beb4a,0x3f74fa0b,0x3f710908,0x3f54db31,0x3f710908,0x3f0e39da,0xbd48fb30,0x3f7ec46d,0x3f7d3aac,0xbf226799,0xbf7853f8,
0x0,0x3e94a031,0x0,0x3f226799,0x3f0e39da,0x3f45e403,0x3f7b14be,0x3f61c598,0x3f6c835e,0x3f7ec46d,0x3ec3ef15,0xbe94a031,0x3f7b14be,0x3f61c598,0xbf54db31,0xbf7ec46d,
0x0,0x3eac7cd4,0x0,0x3f2beb4a,0x3f226799,0x3f5b941a,0x3f7ec46d,0x3f4d9f02,0x3f7b14be,0x3f7d3aac,0x3e47c5c2,0xbf039c3d,0x3f61c598,0x3f2beb4a,0xbf74fa0b,0xbf676bd8,
0x3f803f80,0x0,0x0,0x0,0x3f803f80,0x0,0x0,0x0,0x3f803f80,0x0,0x0,0x0,0x3f803f80,0x0,0x0,0x0,
0x3f353f80,0x3f350000,0xbf350000,0xbf350000,0xbf350000,0x3f353f80,0xbf35bf80,0xbf35bf80,0xbf35bf80,0xbf350000,0x3f350000,0x3f350000,0x3f350000,0xbf35bf80,0x3f353f80,0x3f353f80,
0x3f80,0x3f800000,0xbf800000,0xbf800000,0xbf80,0xbf800000,0x3f800000,0x3f800000,0x3f80,0x3f800000,0xbf800000,0xbf800000,0xbf80,0xbf800000,0x3f800000,0x3f800000,
0xbf353f80,0x3f350000,0xbf350000,0xbf350000,0x3f350000,0x3f35bf80,0xbf353f80,0xbf353f80,0x3f35bf80,0xbf350000,0x3f350000,0x3f350000,0xbf350000,0xbf353f80,0x3f35bf80,0x3f35bf80,
0xbf803f80,0x0,0x0,0x0,0xbf803f80,0x0,0x0,0x0,0xbf803f80,0x0,0x0,0x0,0xbf803f80,0x0,0x0,0x0,
0xbf353f80,0xbf350000,0x3f350000,0x3f350000,0x3f350000,0xbf353f80,0x3f35bf80,0x3f35bf80,0x3f35bf80,0x3f350000,0xbf350000,0xbf350000,0xbf350000,0x3f35bf80,0xbf353f80,0xbf353f80,
0x3f80,0xbf800000,0x3f800000,0x3f800000,0xbf80,0x3f800000,0xbf800000,0xbf800000,0x3f80,0xbf800000,0x3f800000,0x3f800000,0xbf80,0x3f800000,0xbf800000,0xbf800000,
0x3f353f80,0xbf350000,0x3f350000,0x3f350000,0xbf350000,0xbf35bf80,0x3f353f80,0x3f353f80,0xbf35bf80,0x3f350000,0xbf350000,0xbf350000,0x3f350000,0x3f353f80,0xbf35bf80,0xbf35bf80,
0x3f800000,0x3f800000,0x3f800000,0x3f800000,0x3f800000,0x3f800000,0x3f800000,0x3f800000,0x3f800000,0x3f800000,0x3f800000,0x3f800000,0x3f800000,0x3f800000,0x3f800000,0x3f800000,
0x3f800000,0x3f7fb10f,0x3f6c835e,0x3f676bd8,0x3f7ec46d,0x3f7d3aac,0x3f61c598,0x3f5b941a,0x3f7b14be,0x3f7853f8,0x3f54db31,0x3f4d9f02,0x3f74fa0b,0x3f710908,0x3f45e403,0x3f3daef9,
0x3f800000,0x3f7ec46d,0x3f3504f3,0x3f226799,0x3f7b14be,0x3f74fa0b,0x3f0e39da,0x3ef15aea,0x3f6c835e,0x3f61c598,0x3ec3ef15,0x3e94a031,0x3f54db31,0x3f45e403,0x3e47c5c2,0x3dc8bd36,
0x3f800000,0x3f7d3aac,0x3ec3ef15,0x3e78cfcc,0x3f74fa0b,0x3f676bd8,0x3dc8bd36,0xbd48fb30,0x3f54db31,0x3f3daef9,0xbe47c5c2,0xbeac7cd4,0x3f226799,0x3f039c3d,0xbef15aea,0xbf187fc0,
0x3f800000,0x3f7b14be,0x0,0xbe47c5c2,0x3f6c835e,0x3f54db31,0xbec3ef15,0xbf0e39da,0x3f3504f3,0x3f0e39da,0xbf3504f3,0xbf54db31,0x3ec3ef15,0x3e47c5c2,0xbf6c835e,0xbf7b14be,
0x3f800000,0x3f7853f8,0xbec3ef15,0xbf187fc0,0x3f61c598,0x3f3daef9,0xbf45e403,0xbf676bd8,0x3f0e39da,0x3eac7cd4,0xbf7b14be,0xbf7fb10f,0x3dc8bd36,0xbe164083,0xbf74fa0b,0xbf5b941a,
0x3f800000,0x3f74fa0b,0xbf3504f3,0xbf61c598,0x3f54db31,0x3f226799,0xbf7b14be,0xbf7ec46d,0x3ec3ef15,0x3dc8bd36,0xbf6c835e,0xbf45e403,0xbe47c5c2,0xbef15aea,0xbf0e39da,0xbe94a031,
0x3f800000,0x3f710908,0xbf6c835e,0xbf7fb10f,0x3f45e403,0x3f039c3d,0xbf74fa0b,0xbf4d9f02,0x3e47c5c2,0xbe164083,0xbf0e39da,0xbe78cfcc,0xbef15aea,0xbf3daef9,0x3dc8bd36,0x3edae880,
0x0,0x0,0x0,0x0,0x0,0x0,0x0,0x0,0x0,0x0,0x0,0x0,0x0,0x0,0x0,0x0,
0x0,0x3d48fb30,0x3ec3ef15,0x3edae880,0x3dc8bd36,0x3e164083,0x3ef15aea,0x3f039c3d,0x3e47c5c2,0x3e78cfcc,0x3f0e39da,0x3f187fc0,0x3e94a031,0x3eac7cd4,0x3f226799,0x3f2beb4a,
0x0,0x3dc8bd36,0x3f3504f3,0x3f45e403,0x3e47c5c2,0x3e94a031,0x3f54db31,0x3f61c598,0x3ec3ef15,0x3ef15aea,0x3f6c835e,0x3f74fa0b,0x3f0e39da,0x3f226799,0x3f7b14be,0x3f7ec46d,
0x0,0x3e164083,0x3f6c835e,0x3f7853f8,0x3e94a031,0x3edae880,0x3f7ec46d,0x3f7fb10f,0x3f0e39da,0x3f2beb4a,0x3f7b14be,0x3f710908,0x3f45e403,0x3f5b941a,0x3f61c598,0x3f4d9f02,
0x0,0x3e47c5c2,0x3f800000,0x3f7b14be,0x3ec3ef15,0x3f0e39da,0x3f6c835e,0x3f54db31,0x3f3504f3,0x3f54db31,0x3f3504f3,0x3f0e39da,0x3f6c835e,0x3f7b14be,0x3ec3ef15,0x3e47c5c2,
0x0,0x3e78cfcc,0x3f6c835e,0x3f4d9f02,0x3ef15aea,0x3f2beb4a,0x3f226799,0x3edae880,0x3f54db31,0x3f710908,0x3e47c5c2,0xbd48fb30,0x3f7ec46d,0x3f7d3aac,0xbe94a031,0xbf039c3d,
0x0,0x3e94a031,0x3f3504f3,0x3ef15aea,0x3f0e39da,0x3f45e403,0x3e47c5c2,0xbdc8bd36,0x3f6c835e,0x3f7ec46d,0xbec3ef15,0xbf226799,0x3f7b14be,0x3f61c598,0xbf54db31,0xbf74fa0b,
0x0,0x3eac7cd4,0x3ec3ef15,0x3d48fb30,0x3f226799,0x3f5b941a,0xbe94a031,0xbf187fc0,0x3f7b14be,0x3f7d3aac,0xbf54db31,0xbf7853f8,0x3f61c598,0x3f2beb4a,0xbf7ec46d,0xbf676bd8,
0x3f803f80,0xbf803f80,0x3f803f80,0xbf803f80,0x3f803f80,0xbf803f80,0x3f803f80,0xbf803f80,0x3f803f80,0xbf803f80,0x3f803f80,0xbf803f80,0x3f803f80,0xbf803f80,0x3f803f80,0xbf803f80,
0x3f6d3f80,0xbf6d3f80,0xbf6dbf80,0x3f6dbf80,0x3ec43f35,0xbec43f35,0xbec4bf35,0x3ec4bf35,0xbec40000,0x3ec40000,0x3ec40000,0xbec40000,0xbf6dbf35,0x3f6dbf35,0x3f6d3f35,0xbf6d3f35,
0x3f353f80,0xbf353f80,0x3f353f80,0xbf353f80,0xbf350000,0x3f350000,0xbf350000,0x3f350000,0xbf35bf80,0x3f35bf80,0xbf35bf80,0x3f35bf80,0x3f350000,0xbf350000,0x3f350000,0xbf350000,
0x3ec43f80,0xbec43f80,0xbec4bf80,0x3ec4bf80,0xbf6dbf35,0x3f6dbf35,0x3f6d3f35,0xbf6d3f35,0x3f6d0000,0xbf6d0000,0xbf6d0000,0x3f6d0000,0xbec43f35,0x3ec43f35,0x3ec4bf35,0xbec4bf35,
0x3f80,0x3f80,0x3f80,0x3f80,0xbf80,0xbf80,0xbf80,0xbf80,0x3f80,0x3f80,0x3f80,0x3f80,0xbf80,0xbf80,0xbf80,0xbf80,
0xbec43f80,0x3ec43f80,0x3ec4bf80,0xbec4bf80,0x3f6dbf35,0xbf6dbf35,0xbf6d3f35,0x3f6d3f35,0xbf6d0000,0x3f6d0000,0x3f6d0000,0xbf6d0000,0x3ec43f35,0xbec43f35,0xbec4bf35,0x3ec4bf35,
0xbf353f80,0x3f353f80,0xbf353f80,0x3f353f80,0x3f350000,0xbf350000,0x3f350000,0xbf350000,0x3f35bf80,0xbf35bf80,0x3f35bf80,0xbf35bf80,0xbf350000,0x3f350000,0xbf350000,0x3f350000,
0xbf6d3f80,0x3f6d3f80,0x3f6dbf80,0xbf6dbf80,0xbec43f35,0x3ec43f35,0x3ec4bf35,0xbec4bf35,0x3ec40000,0xbec40000,0xbec40000,0x3ec40000,0x3f6dbf35,0xbf6dbf35,0xbf6d3f35,0x3f6d3f35,
0x0,0x0,0x0,0x0,0x0,0x0,0x0,0x0,0x0,0x0,0x0,0x0,0x0,0x0,0x0,0x0,
0x3ec40000,0xbec40000,0xbec40000,0x3ec40000,0x3f6d3f35,0xbf6d3f35,0xbf6dbf35,0x3f6dbf35,0x3f6d3f80,0xbf6d3f80,0xbf6dbf80,0x3f6dbf80,0x3ec43f35,0xbec43f35,0xbec4bf35,0x3ec4bf35,
0x3f350000,0xbf350000,0x3f350000,0xbf350000,0x3f353f80,0xbf353f80,0x3f353f80,0xbf353f80,0xbf350000,0x3f350000,0xbf350000,0x3f350000,0xbf35bf80,0x3f35bf80,0xbf35bf80,0x3f35bf80,
0x3f6d0000,0xbf6d0000,0xbf6d0000,0x3f6d0000,0xbec43f35,0x3ec43f35,0x3ec4bf35,0xbec4bf35,0xbec4bf80,0x3ec4bf80,0x3ec43f80,0xbec43f80,0x3f6d3f35,0xbf6d3f35,0xbf6dbf35,0x3f6dbf35,
0x3f800000,0xbf800000,0x3f800000,0xbf800000,0xbf800000,0x3f800000,0xbf800000,0x3f800000,0x3f800000,0xbf800000,0x3f800000,0xbf800000,0xbf800000,0x3f800000,0xbf800000,0x3f800000,
0x3f6d0000,0xbf6d0000,0xbf6d0000,0x3f6d0000,0xbec4bf35,0x3ec4bf35,0x3ec43f35,0xbec43f35,0xbec43f80,0x3ec43f80,0x3ec4bf80,0xbec4bf80,0x3f6dbf35,0xbf6dbf35,0xbf6d3f35,0x3f6d3f35,
0x3f350000,0xbf350000,0x3f350000,0xbf350000,0x3f35bf80,0xbf35bf80,0x3f35bf80,0xbf35bf80,0xbf350000,0x3f350000,0xbf350000,0x3f350000,0xbf353f80,0x3f353f80,0xbf353f80,0x3f353f80,
0x3ec40000,0xbec40000,0xbec40000,0x3ec40000,0x3f6dbf35,0xbf6dbf35,0xbf6d3f35,0x3f6d3f35,0x3f6dbf80,0xbf6dbf80,0xbf6d3f80,0x3f6d3f80,0x3ec4bf35,0xbec4bf35,0xbec43f35,0x3ec43f35,
0x3f80,0x3f800000,0x3f80,0x3f800000,0x3f80,0x3f800000,0x3f80,0x3f800000,0x3f80,0x3f800000,0x3f80,0x3f800000,0x3f80,0x3f800000,0x3f80,0x3f800000,
0x3f80,0x3f800000,0xbe483f7b,0x3f7b3e48,0xbec43f6d,0x3f6d3ec4,0xbf0e3f55,0x3f553f0e,0xbf353f35,0x3f353f35,0xbf553f0e,0x3f0e3f55,0xbf6d3ec4,0x3ec43f6d,0xbf7b3e48,0x3e483f7b,
0x3f80,0x3f800000,0xbf800000,0x3f80,0xbf80,0xbf800000,0x3f800000,0xbf80,0x3f80,0x3f800000,0xbf800000,0x3f80,0xbf80,0xbf800000,0x3f800000,0xbf80,
0x3f80,0x3f800000,0xbf7bbe48,0xbe483f7b,0x3ec4bf6d,0xbf6dbec4,0x3f553f0e,0x3f0ebf55,0xbf353f35,0x3f353f35,0xbf0ebf55,0xbf553f0e,0x3f6dbec4,0xbec4bf6d,0x3e483f7b,0x3f7bbe48,
0x3f80,0x3f800000,0xbf80,0xbf800000,0x3f80,0x3f800000,0xbf80,0xbf800000,0x3f80,0x3f800000,0xbf80,0xbf800000,0x3f80,0x3f800000,0xbf80,0xbf800000,
0x3f80,0x3f800000,0x3e48bf7b,0xbf7bbe48,0xbec43f6d,0x3f6d3ec4,0x3f0ebf55,0xbf55bf0e,0xbf353f35,0x3f353f35,0x3f55bf0e,0xbf0ebf55,0xbf6d3ec4,0x3ec43f6d,0x3f7bbe48,0xbe48bf7b,
0x3f80,0x3f800000,0x3f800000,0xbf80,0xbf80,0xbf800000,0xbf800000,0x3f80,0x3f80,0x3f800000,0x3f800000,0xbf80,0xbf80,0xbf800000,0xbf800000,0x3f80,
0x3f80,0x3f800000,0x3f7b3e48,0x3e48bf7b,0x3ec4bf6d,0xbf6dbec4,0xbf55bf0e,0xbf0e3f55,0xbf353f35,0x3f353f35,0x3f0e3f55,0x3f55bf0e,0x3f6dbec4,0xbec4bf6d,0xbe48bf7b,0xbf7b3e48,
0x3f80,0x3f800000,0x3f80,0x3f800000,0x3f80,0x3f800000,0x3f80,0x3f800000,0x3f80,0x3f800000,0x3f80,0x3f800000,0x3f80,0x3f800000,0x3f80,0x3f800000,
0xbf800000,0x3f80,0xbf7bbe48,0xbe483f7b,0xbf6dbec4,0xbec43f6d,0xbf55bf0e,0xbf0e3f55,0xbf35bf35,0xbf353f35,0xbf0ebf55,0xbf553f0e,0xbec4bf6d,0xbf6d3ec4,0xbe48bf7b,0xbf7b3e48,
0x3f80,0x3f800000,0xbf800000,0x3f80,0xbf80,0xbf800000,0x3f800000,0xbf80,0x3f80,0x3f800000,0xbf800000,0x3f80,0xbf80,0xbf800000,0x3f800000,0xbf80,
0xbf800000,0x3f80,0x3e48bf7b,0xbf7bbe48,0x3f6d3ec4,0x3ec4bf6d,0xbf0e3f55,0x3f553f0e,0xbf35bf35,0xbf353f35,0x3f55bf0e,0xbf0ebf55,0x3ec43f6d,0x3f6dbec4,0xbf7b3e48,0x3e483f7b,
0x3f80,0x3f800000,0xbf80,0xbf800000,0x3f80,0x3f800000,0xbf80,0xbf800000,0x3f80,0x3f800000,0xbf80,0xbf800000,0x3f80,0x3f800000,0xbf80,0xbf800000,
0xbf800000,0x3f80,0x3f7b3e48,0x3e48bf7b,0xbf6dbec4,0xbec43f6d,0x3f553f0e,0x3f0ebf55,0xbf35bf35,0xbf353f35,0x3f0e3f55,0x3f55bf0e,0xbec4bf6d,0xbf6d3ec4,0x3e483f7b,0x3f7bbe48,
0x3f80,0x3f800000,0x3f800000,0xbf80,0xbf80,0xbf800000,0xbf800000,0x3f80,0x3f80,0x3f800000,0x3f800000,0xbf80,0xbf80,0xbf800000,0xbf800000,0x3f80,
0xbf800000,0x3f80,0xbe483f7b,0x3f7b3e48,0x3f6d3ec4,0x3ec4bf6d,0x3f0ebf55,0xbf55bf0e,0xbf35bf35,0xbf353f35,0xbf553f0e,0x3f0e3f55,0x3ec43f6d,0x3f6dbec4,0x3f7bbe48,0xbe48bf7b,
0x3f80,0xbf800000,0x3f80,0xbf800000,0x3f80,0xbf800000,0x3f80,0xbf800000,0x3f80,0xbf800000,0x3f80,0xbf800000,0x3f80,0xbf800000,0x3f80,0xbf800000,
0xbe483f7b,0xbf7bbe48,0xbec43f6d,0xbf6dbec4,0xbf0e3f55,0xbf55bf0e,0xbf353f35,0xbf35bf35,0xbf553f0e,0xbf0ebf55,0xbf6d3ec4,0xbec4bf6d,0xbf7b3e48,0xbe48bf7b,0xbf800000,0xbf80,
0xbf800000,0xbf80,0xbf80,0x3f800000,0x3f800000,0x3f80,0x3f80,0xbf800000,0xbf800000,0xbf80,0xbf80,0x3f800000,0x3f800000,0x3f80,0x3f80,0xbf800000,
0xbf7bbe48,0x3e48bf7b,0x3ec4bf6d,0x3f6d3ec4,0x3f553f0e,0xbf0e3f55,0xbf353f35,0xbf35bf35,0xbf0ebf55,0x3f55bf0e,0x3f6dbec4,0x3ec43f6d,0x3e483f7b,0xbf7b3e48,0xbf800000,0xbf80,
0xbf80,0x3f800000,0x3f80,0xbf800000,0xbf80,0x3f800000,0x3f80,0xbf800000,0xbf80,0x3f800000,0x3f80,0xbf800000,0xbf80,0x3f800000,0x3f80,0xbf800000,
0x3e48bf7b,0x3f7b3e48,0xbec43f6d,0xbf6dbec4,0x3f0ebf55,0x3f553f0e,0xbf353f35,0xbf35bf35,0x3f55bf0e,0x3f0e3f55,0xbf6d3ec4,0xbec4bf6d,0x3f7bbe48,0x3e483f7b,0xbf800000,0xbf80,
0x3f800000,0x3f80,0xbf80,0x3f800000,0xbf800000,0xbf80,0x3f80,0xbf800000,0x3f800000,0x3f80,0xbf80,0x3f800000,0xbf800000,0xbf80,0x3f80,0xbf800000,
0x3f7b3e48,0xbe483f7b,0x3ec4bf6d,0x3f6d3ec4,0xbf55bf0e,0x3f0ebf55,0xbf353f35,0xbf35bf35,0x3f0e3f55,0xbf553f0e,0x3f6dbec4,0x3ec43f6d,0xbe48bf7b,0x3f7bbe48,0xbf800000,0xbf80,
0x3f80,0xbf800000,0x3f80,0xbf800000,0x3f80,0xbf800000,0x3f80,0xbf800000,0x3f80,0xbf800000,0x3f80,0xbf800000,0x3f80,0xbf800000,0x3f80,0xbf800000,
0xbf7bbe48,0x3e48bf7b,0xbf6dbec4,0x3ec4bf6d,0xbf55bf0e,0x3f0ebf55,0xbf35bf35,0x3f35bf35,0xbf0ebf55,0x3f55bf0e,0xbec4bf6d,0x3f6dbec4,0xbe48bf7b,0x3f7bbe48,0xbf80,0x3f800000,
0xbf800000,0xbf80,0xbf80,0x3f800000,0x3f800000,0x3f80,0x3f80,0xbf800000,0xbf800000,0xbf80,0xbf80,0x3f800000,0x3f800000,0x3f80,0x3f80,0xbf800000,
0x3e48bf7b,0x3f7b3e48,0x3f6d3ec4,0xbec43f6d,0xbf0e3f55,0xbf55bf0e,0xbf35bf35,0x3f35bf35,0x3f55bf0e,0x3f0e3f55,0x3ec43f6d,0xbf6d3ec4,0xbf7b3e48,0xbe48bf7b,0xbf80,0x3f800000,
0xbf80,0x3f800000,0x3f80,0xbf800000,0xbf80,0x3f800000,0x3f80,0xbf800000,0xbf80,0x3f800000,0x3f80,0xbf800000,0xbf80,0x3f800000,0x3f80,0xbf800000,
0x3f7b3e48,0xbe483f7b,0xbf6dbec4,0x3ec4bf6d,0x3f553f0e,0xbf0e3f55,0xbf35bf35,0x3f35bf35,0x3f0e3f55,0xbf553f0e,0xbec4bf6d,0x3f6dbec4,0x3e483f7b,0xbf7b3e48,0xbf80,0x3f800000,
0x3f800000,0x3f80,0xbf80,0x3f800000,0xbf800000,0xbf80,0x3f80,0xbf800000,0x3f800000,0x3f80,0xbf80,0x3f800000,0xbf800000,0xbf80,0x3f80,0xbf800000,
0xbe483f7b,0xbf7bbe48,0x3f6d3ec4,0xbec43f6d,0x3f0ebf55,0x3f553f0e,0xbf35bf35,0x3f35bf35,0xbf553f0e,0xbf0ebf55,0x3ec43f6d,0xbf6d3ec4,0x3f7bbe48,0x3e483f7b,0xbf80,0x3f800000,
0x3f80,0x3f800000,0xbec43f6d,0x3f6d3ec4,0xbf353f35,0x3f353f35,0xbf6d3ec4,0x3ec43f6d,0xbf800000,0x3f80,0xbf6dbec4,0xbec43f6d,0xbf35bf35,0xbf353f35,0xbec4bf6d,0xbf6d3ec4,
0x3f80,0x3f800000,0xbf0e3f55,0x3f553f0e,0xbf6d3ec4,0x3ec43f6d,0xbf7bbe48,0xbe483f7b,0xbf35bf35,0xbf353f35,0xbe48bf7b,0xbf7b3e48,0x3ec4bf6d,0xbf6dbec4,0x3f55bf0e,0xbf0ebf55,
0x3f80,0x3f800000,0xbf6dbec4,0xbec43f6d,0x3f35bf35,0xbf35bf35,0x3ec43f6d,0x3f6dbec4,0xbf800000,0x3f80,0x3ec4bf6d,0xbf6dbec4,0x3f353f35,0x3f35bf35,0xbf6d3ec4,0x3ec43f6d,
0x3f80,0x3f800000,0xbf55bf0e,0xbf0e3f55,0x3f6dbec4,0xbec4bf6d,0xbe483f7b,0x3f7b3e48,0xbf35bf35,0xbf353f35,0x3f7bbe48,0xbe48bf7b,0xbec43f6d,0x3f6d3ec4,0xbf0ebf55,0xbf553f0e,
0x3f80,0x3f800000,0x3ec4bf6d,0xbf6dbec4,0xbf353f35,0x3f353f35,0x3f6dbec4,0xbec4bf6d,0xbf800000,0x3f80,0x3f6d3ec4,0x3ec4bf6d,0xbf35bf35,0xbf353f35,0x3ec43f6d,0x3f6dbec4,
0x3f80,0x3f800000,0x3f0ebf55,0xbf55bf0e,0xbf6d3ec4,0x3ec43f6d,0x3f7b3e48,0x3e48bf7b,0xbf35bf35,0xbf353f35,0x3e483f7b,0x3f7bbe48,0x3ec4bf6d,0xbf6dbec4,0xbf553f0e,0x3f0e3f55,
0x3f80,0x3f800000,0x3f6d3ec4,0x3ec4bf6d,0x3f35bf35,0xbf35bf35,0xbec4bf6d,0xbf6d3ec4,0xbf800000,0x3f80,0xbec43f6d,0x3f6d3ec4,0x3f353f35,0x3f35bf35,0x3f6dbec4,0xbec4bf6d,
0x3f80,0x3f800000,0x3f553f0e,0x3f0ebf55,0x3f6dbec4,0xbec4bf6d,0x3e48bf7b,0xbf7bbe48,0xbf35bf35,0xbf353f35,0xbf7b3e48,0x3e483f7b,0xbec43f6d,0x3f6d3ec4,0x3f0e3f55,0x3f55bf0e,
0xbf80,0xbf800000,0x3ec4bf6d,0xbf6dbec4,0x3f35bf35,0xbf35bf35,0x3f6dbec4,0xbec4bf6d,0x3f800000,0xbf80,0x3f6d3ec4,0x3ec4bf6d,0x3f353f35,0x3f35bf35,0x3ec43f6d,0x3f6dbec4,
0x3f800000,0xbf80,0x3f553f0e,0x3f0ebf55,0x3ec43f6d,0x3f6dbec4,0xbe483f7b,0x3f7b3e48,0xbf353f35,0x3f353f35,0xbf7b3e48,0x3e483f7b,0xbf6dbec4,0xbec43f6d,0xbf0ebf55,0xbf553f0e,
0xbf80,0xbf800000,0x3f6d3ec4,0x3ec4bf6d,0xbf353f35,0x3f353f35,0xbec4bf6d,0xbf6d3ec4,0x3f800000,0xbf80,0xbec43f6d,0x3f6d3ec4,0xbf35bf35,0xbf353f35,0x3f6dbec4,0xbec4bf6d,
0x3f800000,0xbf80,0xbf0e3f55,0x3f553f0e,0xbec4bf6d,0xbf6d3ec4,0x3f7b3e48,0x3e48bf7b,0xbf353f35,0x3f353f35,0xbe48bf7b,0xbf7b3e48,0x3f6d3ec4,0x3ec4bf6d,0xbf553f0e,0x3f0e3f55,
0xbf80,0xbf800000,0xbec43f6d,0x3f6d3ec4,0x3f35bf35,0xbf35bf35,0xbf6d3ec4,0x3ec43f6d,0x3f800000,0xbf80,0xbf6dbec4,0xbec43f6d,0x3f353f35,0x3f35bf35,0xbec4bf6d,0xbf6d3ec4,
0x3f800000,0xbf80,0xbf55bf0e,0xbf0e3f55,0x3ec43f6d,0x3f6dbec4,0x3e48bf7b,0xbf7bbe48,0xbf353f35,0x3f353f35,0x3f7bbe48,0xbe48bf7b,0xbf6dbec4,0xbec43f6d,0x3f0e3f55,0x3f55bf0e,
0xbf80,0xbf800000,0xbf6dbec4,0xbec43f6d,0xbf353f35,0x3f353f35,0x3ec43f6d,0x3f6dbec4,0x3f800000,0xbf80,0x3ec4bf6d,0xbf6dbec4,0xbf35bf35,0xbf353f35,0xbf6d3ec4,0x3ec43f6d,
0x3f800000,0xbf80,0x3f0ebf55,0xbf55bf0e,0xbec4bf6d,0xbf6d3ec4,0xbf7bbe48,0xbe483f7b,0xbf353f35,0x3f353f35,0x3e483f7b,0x3f7bbe48,0x3f6d3ec4,0x3ec4bf6d,0x3f55bf0e,0xbf0ebf55,
0xbec43f6d,0xbf6dbec4,0xbf353f35,0xbf35bf35,0xbf6d3ec4,0xbec4bf6d,0xbf800000,0xbf80,0xbf6dbec4,0x3ec4bf6d,0xbf35bf35,0x3f35bf35,0xbec4bf6d,0x3f6dbec4,0xbf80,0x3f800000,
0xbf0e3f55,0xbf55bf0e,0xbf6d3ec4,0xbec4bf6d,0xbf7bbe48,0x3e48bf7b,0xbf35bf35,0x3f35bf35,0xbe48bf7b,0x3f7bbe48,0x3ec4bf6d,0x3f6d3ec4,0x3f55bf0e,0x3f0e3f55,0x3f800000,0x3f80,
0xbf6dbec4,0x3ec4bf6d,0x3f35bf35,0x3f353f35,0x3ec43f6d,0xbf6d3ec4,0xbf800000,0xbf80,0x3ec4bf6d,0x3f6d3ec4,0x3f353f35,0xbf353f35,0xbf6d3ec4,0xbec4bf6d,0xbf80,0x3f800000,
0xbf55bf0e,0x3f0ebf55,0x3f6dbec4,0x3ec43f6d,0xbe483f7b,0xbf7bbe48,0xbf35bf35,0x3f35bf35,0x3f7bbe48,0x3e483f7b,0xbec43f6d,0xbf6dbec4,0xbf0ebf55,0x3f55bf0e,0x3f800000,0x3f80,
0x3ec4bf6d,0x3f6d3ec4,0xbf353f35,0xbf35bf35,0x3f6dbec4,0x3ec43f6d,0xbf800000,0xbf80,0x3f6d3ec4,0xbec43f6d,0xbf35bf35,0x3f35bf35,0x3ec43f6d,0xbf6d3ec4,0xbf80,0x3f800000,
0x3f0ebf55,0x3f553f0e,0xbf6d3ec4,0xbec4bf6d,0x3f7b3e48,0xbe483f7b,0xbf35bf35,0x3f35bf35,0x3e483f7b,0xbf7b3e48,0x3ec4bf6d,0x3f6d3ec4,0xbf553f0e,0xbf0ebf55,0x3f800000,0x3f80,
0x3f6d3ec4,0xbec43f6d,0x3f35bf35,0x3f353f35,0xbec4bf6d,0x3f6dbec4,0xbf800000,0xbf80,0xbec43f6d,0xbf6dbec4,0x3f353f35,0xbf353f35,0x3f6dbec4,0x3ec43f6d,0xbf80,0x3f800000,
0x3f553f0e,0xbf0e3f55,0x3f6dbec4,0x3ec43f6d,0x3e48bf7b,0x3f7b3e48,0xbf35bf35,0x3f35bf35,0xbf7b3e48,0xbe48bf7b,0xbec43f6d,0xbf6dbec4,0x3f0e3f55,0xbf553f0e,0x3f800000,0x3f80,
0x3ec4bf6d,0x3f6d3ec4,0x3f35bf35,0x3f353f35,0x3f6dbec4,0x3ec43f6d,0x3f800000,0x3f80,0x3f6d3ec4,0xbec43f6d,0x3f353f35,0xbf353f35,0x3ec43f6d,0xbf6d3ec4,0x3f80,0xbf800000,
0x3f553f0e,0xbf0e3f55,0x3ec43f6d,0xbf6d3ec4,0xbe483f7b,0xbf7bbe48,0xbf353f35,0xbf35bf35,0xbf7b3e48,0xbe48bf7b,0xbf6dbec4,0x3ec4bf6d,0xbf0ebf55,0x3f55bf0e,0xbf80,0x3f800000,
0x3f6d3ec4,0xbec43f6d,0xbf353f35,0xbf35bf35,0xbec4bf6d,0x3f6dbec4,0x3f800000,0x3f80,0xbec43f6d,0xbf6dbec4,0xbf35bf35,0x3f35bf35,0x3f6dbec4,0x3ec43f6d,0x3f80,0xbf800000,
0xbf0e3f55,0xbf55bf0e,0xbec4bf6d,0x3f6dbec4,0x3f7b3e48,0xbe483f7b,0xbf353f35,0xbf35bf35,0xbe48bf7b,0x3f7bbe48,0x3f6d3ec4,0xbec43f6d,0xbf553f0e,0xbf0ebf55,0xbf80,0x3f800000,
0xbec43f6d,0xbf6dbec4,0x3f35bf35,0x3f353f35,0xbf6d3ec4,0xbec4bf6d,0x3f800000,0x3f80,0xbf6dbec4,0x3ec4bf6d,0x3f353f35,0xbf353f35,0xbec4bf6d,0x3f6dbec4,0x3f80,0xbf800000,
0xbf55bf0e,0x3f0ebf55,0x3ec43f6d,0xbf6d3ec4,0x3e48bf7b,0x3f7b3e48,0xbf353f35,0xbf35bf35,0x3f7bbe48,0x3e483f7b,0xbf6dbec4,0x3ec4bf6d,0x3f0e3f55,0xbf553f0e,0xbf80,0x3f800000,
0xbf6dbec4,0x3ec4bf6d,0xbf353f35,0xbf35bf35,0x3ec43f6d,0xbf6d3ec4,0x3f800000,0x3f80,0x3ec4bf6d,0x3f6d3ec4,0xbf35bf35,0x3f35bf35,0xbf6d3ec4,0xbec4bf6d,0x3f80,0xbf800000,
0x3f0ebf55,0x3f553f0e,0xbec4bf6d,0x3f6dbec4,0xbf7bbe48,0x3e48bf7b,0xbf353f35,0xbf35bf35,0x3e483f7b,0xbf7b3e48,0x3f6d3ec4,0xbec43f6d,0x3f55bf0e,0x3f0e3f55,0xbf80,0x3f800000,
0x3f80,0x3f800000,0xbf353f35,0x3f353f35,0xbf800000,0x3f80,0xbf35bf35,0xbf353f35,0xbf80,0xbf800000,0x3f35bf35,0xbf35bf35,0x3f800000,0xbf80,0x3f353f35,0x3f35bf35,
0x3f80,0x3f800000,0xbf553f0e,0x3f0e3f55,0xbf6dbec4,0xbec43f6d,0xbe48bf7b,0xbf7b3e48,0x3f35bf35,0xbf35bf35,0x3f7b3e48,0x3e48bf7b,0x3ec43f6d,0x3f6dbec4,0xbf0e3f55,0x3f553f0e,
0x3f80,0x3f800000,0xbf35bf35,0xbf353f35,0x3f800000,0xbf80,0xbf353f35,0x3f353f35,0xbf80,0xbf800000,0x3f353f35,0x3f35bf35,0xbf800000,0x3f80,0x3f35bf35,0xbf35bf35,
0x3f80,0x3f800000,0xbf0ebf55,0xbf553f0e,0x3f6d3ec4,0x3ec4bf6d,0xbf7b3e48,0x3e483f7b,0x3f35bf35,0xbf35bf35,0xbe483f7b,0x3f7b3e48,0xbec4bf6d,0xbf6d3ec4,0x3f553f0e,0x3f0ebf55,
0x3f80,0x3f800000,0x3f35bf35,0xbf35bf35,0xbf800000,0x3f80,0x3f353f35,0x3f35bf35,0xbf80,0xbf800000,0xbf353f35,0x3f353f35,0x3f800000,0xbf80,0xbf35bf35,0xbf353f35,
0x3f80,0x3f800000,0x3f55bf0e,0xbf0ebf55,0xbf6dbec4,0xbec43f6d,0x3e483f7b,0x3f7bbe48,0x3f35bf35,0xbf35bf35,0xbf7bbe48,0xbe483f7b,0x3ec43f6d,0x3f6dbec4,0x3f0ebf55,0xbf55bf0e,
0x3f80,0x3f800000,0x3f353f35,0x3f35bf35,0x3f800000,0xbf80,0x3f35bf35,0xbf35bf35,0xbf80,0xbf800000,0xbf35bf35,0xbf353f35,0xbf800000,0x3f80,0xbf353f35,0x3f353f35,
0x3f80,0x3f800000,0x3f0e3f55,0x3f55bf0e,0x3f6d3ec4,0x3ec4bf6d,0x3f7bbe48,0xbe48bf7b,0x3f35bf35,0xbf35bf35,0x3e48bf7b,0xbf7bbe48,0xbec4bf6d,0xbf6d3ec4,0xbf55bf0e,0xbf0e3f55,
0x3f80,0x3f800000,0xbf353f35,0x3f353f35,0xbf800000,0x3f80,0xbf35bf35,0xbf353f35,0xbf80,0xbf800000,0x3f35bf35,0xbf35bf35,0x3f800000,0xbf80,0x3f353f35,0x3f35bf35,
0xbf800000,0x3f80,0xbf0ebf55,0xbf553f0e,0x3ec4bf6d,0xbf6dbec4,0x3f7bbe48,0xbe48bf7b,0x3f353f35,0x3f35bf35,0xbe483f7b,0x3f7b3e48,0xbf6d3ec4,0x3ec43f6d,0xbf55bf0e,0xbf0e3f55,
0x3f80,0x3f800000,0xbf35bf35,0xbf353f35,0x3f800000,0xbf80,0xbf353f35,0x3f353f35,0xbf80,0xbf800000,0x3f353f35,0x3f35bf35,0xbf800000,0x3f80,0x3f35bf35,0xbf35bf35,
0xbf800000,0x3f80,0x3f55bf0e,0xbf0ebf55,0xbec43f6d,0x3f6d3ec4,0xbe48bf7b,0xbf7b3e48,0x3f353f35,0x3f35bf35,0xbf7bbe48,0xbe483f7b,0x3f6dbec4,0xbec4bf6d,0xbf0e3f55,0x3f553f0e,
0x3f80,0x3f800000,0x3f35bf35,0xbf35bf35,0xbf800000,0x3f80,0x3f353f35,0x3f35bf35,0xbf80,0xbf800000,0xbf353f35,0x3f353f35,0x3f800000,0xbf80,0xbf35bf35,0xbf353f35,
0xbf800000,0x3f80,0x3f0e3f55,0x3f55bf0e,0x3ec4bf6d,0xbf6dbec4,0xbf7b3e48,0x3e483f7b,0x3f353f35,0x3f35bf35,0x3e48bf7b,0xbf7bbe48,0xbf6d3ec4,0x3ec43f6d,0x3f553f0e,0x3f0ebf55,
0x3f80,0x3f800000,0x3f353f35,0x3f35bf35,0x3f800000,0xbf80,0x3f35bf35,0xbf35bf35,0xbf80,0xbf800000,0xbf35bf35,0xbf353f35,0xbf800000,0x3f80,0xbf353f35,0x3f353f35,
0xbf800000,0x3f80,0xbf553f0e,0x3f0e3f55,0xbec43f6d,0x3f6d3ec4,0x3e483f7b,0x3f7bbe48,0x3f353f35,0x3f35bf35,0x3f7b3e48,0x3e48bf7b,0x3f6dbec4,0xbec4bf6d,0x3f0ebf55,0xbf55bf0e,
0xbf353f35,0xbf35bf35,0xbf800000,0xbf80,0xbf35bf35,0x3f35bf35,0xbf80,0x3f800000,0x3f35bf35,0x3f353f35,0x3f800000,0x3f80,0x3f353f35,0xbf353f35,0x3f80,0xbf800000,
0xbf553f0e,0xbf0ebf55,0xbf6dbec4,0x3ec4bf6d,0xbe48bf7b,0x3f7bbe48,0x3f35bf35,0x3f353f35,0x3f7b3e48,0xbe483f7b,0x3ec43f6d,0xbf6d3ec4,0xbf0e3f55,0xbf55bf0e,0xbf800000,0xbf80,
0xbf35bf35,0x3f35bf35,0x3f800000,0x3f80,0xbf353f35,0xbf35bf35,0xbf80,0x3f800000,0x3f353f35,0xbf353f35,0xbf800000,0xbf80,0x3f35bf35,0x3f353f35,0x3f80,0xbf800000,
0xbf0ebf55,0x3f55bf0e,0x3f6d3ec4,0xbec43f6d,0xbf7b3e48,0xbe48bf7b,0x3f35bf35,0x3f353f35,0xbe483f7b,0xbf7bbe48,0xbec4bf6d,0x3f6dbec4,0x3f553f0e,0xbf0e3f55,0xbf800000,0xbf80,
0x3f35bf35,0x3f353f35,0xbf800000,0xbf80,0x3f353f35,0xbf353f35,0xbf80,0x3f800000,0xbf353f35,0xbf35bf35,0x3f800000,0x3f80,0xbf35bf35,0x3f35bf35,0x3f80,0xbf800000,
0x3f55bf0e,0x3f0e3f55,0xbf6dbec4,0x3ec4bf6d,0x3e483f7b,0xbf7b3e48,0x3f35bf35,0x3f353f35,0xbf7bbe48,0x3e48bf7b,0x3ec43f6d,0xbf6d3ec4,0x3f0ebf55,0x3f553f0e,0xbf800000,0xbf80,
0x3f353f35,0xbf353f35,0x3f800000,0x3f80,0x3f35bf35,0x3f353f35,0xbf80,0x3f800000,0xbf35bf35,0x3f35bf35,0xbf800000,0xbf80,0xbf353f35,0xbf35bf35,0x3f80,0xbf800000,
0x3f0e3f55,0xbf553f0e,0x3f6d3ec4,0xbec43f6d,0x3f7bbe48,0x3e483f7b,0x3f35bf35,0x3f353f35,0x3e48bf7b,0x3f7b3e48,0xbec4bf6d,0x3f6dbec4,0xbf55bf0e,0x3f0ebf55,0xbf800000,0xbf80,
0xbf353f35,0xbf35bf35,0xbf800000,0xbf80,0xbf35bf35,0x3f35bf35,0xbf80,0x3f800000,0x3f35bf35,0x3f353f35,0x3f800000,0x3f80,0x3f353f35,0xbf353f35,0x3f80,0xbf800000,
0xbf0ebf55,0x3f55bf0e,0x3ec4bf6d,0x3f6d3ec4,0x3f7bbe48,0x3e483f7b,0x3f353f35,0xbf353f35,0xbe483f7b,0xbf7bbe48,0xbf6d3ec4,0xbec4bf6d,0xbf55bf0e,0x3f0ebf55,0xbf80,0x3f800000,
0xbf35bf35,0x3f35bf35,0x3f800000,0x3f80,0xbf353f35,0xbf35bf35,0xbf80,0x3f800000,0x3f353f35,0xbf353f35,0xbf800000,0xbf80,0x3f35bf35,0x3f353f35,0x3f80,0xbf800000,
0x3f55bf0e,0x3f0e3f55,0xbec43f6d,0xbf6dbec4,0xbe48bf7b,0x3f7bbe48,0x3f353f35,0xbf353f35,0xbf7bbe48,0x3e48bf7b,0x3f6dbec4,0x3ec43f6d,0xbf0e3f55,0xbf55bf0e,0xbf80,0x3f800000,
0x3f35bf35,0x3f353f35,0xbf800000,0xbf80,0x3f353f35,0xbf353f35,0xbf80,0x3f800000,0xbf353f35,0xbf35bf35,0x3f800000,0x3f80,0xbf35bf35,0x3f35bf35,0x3f80,0xbf800000,
0x3f0e3f55,0xbf553f0e,0x3ec4bf6d,0x3f6d3ec4,0xbf7b3e48,0xbe48bf7b,0x3f353f35,0xbf353f35,0x3e48bf7b,0x3f7b3e48,0xbf6d3ec4,0xbec4bf6d,0x3f553f0e,0xbf0e3f55,0xbf80,0x3f800000,
0x3f353f35,0xbf353f35,0x3f800000,0x3f80,0x3f35bf35,0x3f353f35,0xbf80,0x3f800000,0xbf35bf35,0x3f35bf35,0xbf800000,0xbf80,0xbf353f35,0xbf35bf35,0x3f80,0xbf800000,
0xbf553f0e,0xbf0ebf55,0xbec43f6d,0xbf6dbec4,0x3e483f7b,0xbf7b3e48,0x3f353f35,0xbf353f35,0x3f7b3e48,0xbe483f7b,0x3f6dbec4,0x3ec43f6d,0x3f0ebf55,0x3f553f0e,0xbf80,0x3f800000,
0x3f80,0x3f800000,0xbf6d3ec4,0x3ec43f6d,0xbf35bf35,0xbf353f35,0x3ec4bf6d,0xbf6dbec4,0x3f800000,0xbf80,0x3ec43f6d,0x3f6dbec4,0xbf353f35,0x3f353f35,0xbf6dbec4,0xbec43f6d,
0x3f80,0x3f800000,0xbf7b3e48,0x3e483f7b,0xbec4bf6d,0xbf6d3ec4,0x3f55bf0e,0xbf0ebf55,0x3f353f35,0x3f35bf35,0xbf0e3f55,0x3f553f0e,0xbf6dbec4,0xbec43f6d,0x3e48bf7b,0xbf7bbe48,
0x3f80,0x3f800000,0xbec4bf6d,0xbf6d3ec4,0x3f353f35,0x3f35bf35,0xbf6dbec4,0xbec43f6d,0x3f800000,0xbf80,0xbf6d3ec4,0x3ec43f6d,0x3f35bf35,0xbf35bf35,0xbec43f6d,0x3f6d3ec4,
0x3f80,0x3f800000,0xbe48bf7b,0xbf7b3e48,0x3ec43f6d,0x3f6dbec4,0xbf0ebf55,0xbf553f0e,0x3f353f35,0x3f35bf35,0xbf55bf0e,0xbf0e3f55,0x3f6d3ec4,0x3ec4bf6d,0xbf7bbe48,0xbe483f7b,
0x3f80,0x3f800000,0x3f6dbec4,0xbec4bf6d,0xbf35bf35,0xbf353f35,0xbec43f6d,0x3f6d3ec4,0x3f800000,0xbf80,0xbec4bf6d,0xbf6d3ec4,0xbf353f35,0x3f353f35,0x3f6d3ec4,0x3ec4bf6d,
0x3f80,0x3f800000,0x3f7bbe48,0xbe48bf7b,0xbec4bf6d,0xbf6d3ec4,0xbf553f0e,0x3f0e3f55,0x3f353f35,0x3f35bf35,0x3f0ebf55,0xbf55bf0e,0xbf6dbec4,0xbec43f6d,0xbe483f7b,0x3f7b3e48,
0x3f80,0x3f800000,0x3ec43f6d,0x3f6dbec4,0x3f353f35,0x3f35bf35,0x3f6d3ec4,0x3ec4bf6d,0x3f800000,0xbf80,0x3f6dbec4,0xbec4bf6d,0x3f35bf35,0xbf35bf35,0x3ec4bf6d,0xbf6dbec4,
0x3f80,0x3f800000,0x3e483f7b,0x3f7bbe48,0x3ec43f6d,0x3f6dbec4,0x3f0e3f55,0x3f55bf0e,0x3f353f35,0x3f35bf35,0x3f553f0e,0x3f0ebf55,0x3f6d3ec4,0x3ec4bf6d,0x3f7b3e48,0x3e48bf7b,
0xbf80,0xbf800000,0x3f6dbec4,0xbec4bf6d,0x3f353f35,0x3f35bf35,0xbec43f6d,0x3f6d3ec4,0xbf800000,0x3f80,0xbec4bf6d,0xbf6d3ec4,0x3f35bf35,0xbf35bf35,0x3f6d3ec4,0x3ec4bf6d,
0x3f800000,0xbf80,0x3e483f7b,0x3f7bbe48,0xbf6d3ec4,0x3ec43f6d,0xbf0ebf55,0xbf553f0e,0x3f35bf35,0xbf35bf35,0x3f553f0e,0x3f0ebf55,0xbec43f6d,0x3f6d3ec4,0xbf7bbe48,0xbe483f7b,
0xbf80,0xbf800000,0x3ec43f6d,0x3f6dbec4,0xbf35bf35,0xbf353f35,0x3f6d3ec4,0x3ec4bf6d,0xbf800000,0x3f80,0x3f6dbec4,0xbec4bf6d,0xbf353f35,0x3f353f35,0x3ec4bf6d,0xbf6dbec4,
0x3f800000,0xbf80,0xbf7b3e48,0x3e483f7b,0x3f6dbec4,0xbec4bf6d,0xbf553f0e,0x3f0e3f55,0x3f35bf35,0xbf35bf35,0xbf0e3f55,0x3f553f0e,0x3ec4bf6d,0xbf6dbec4,0xbe483f7b,0x3f7b3e48,
0xbf80,0xbf800000,0xbf6d3ec4,0x3ec43f6d,0x3f353f35,0x3f35bf35,0x3ec4bf6d,0xbf6dbec4,0xbf800000,0x3f80,0x3ec43f6d,0x3f6dbec4,0x3f35bf35,0xbf35bf35,0xbf6dbec4,0xbec43f6d,
0x3f800000,0xbf80,0xbe48bf7b,0xbf7b3e48,0xbf6d3ec4,0x3ec43f6d,0x3f0e3f55,0x3f55bf0e,0x3f35bf35,0xbf35bf35,0xbf55bf0e,0xbf0e3f55,0xbec43f6d,0x3f6d3ec4,0x3f7b3e48,0x3e48bf7b,
0xbf80,0xbf800000,0xbec4bf6d,0xbf6d3ec4,0xbf35bf35,0xbf353f35,0xbf6dbec4,0xbec43f6d,0xbf800000,0x3f80,0xbf6d3ec4,0x3ec43f6d,0xbf353f35,0x3f353f35,0xbec43f6d,0x3f6d3ec4,
0x3f800000,0xbf80,0x3f7bbe48,0xbe48bf7b,0x3f6dbec4,0xbec4bf6d,0x3f55bf0e,0xbf0ebf55,0x3f35bf35,0xbf35bf35,0x3f0ebf55,0xbf55bf0e,0x3ec4bf6d,0xbf6dbec4,0x3e48bf7b,0xbf7bbe48,
0xbf6d3ec4,0xbec4bf6d,0xbf35bf35,0x3f35bf35,0x3ec4bf6d,0x3f6d3ec4,0x3f800000,0x3f80,0x3ec43f6d,0xbf6d3ec4,0xbf353f35,0xbf35bf35,0xbf6dbec4,0x3ec4bf6d,0xbf80,0x3f800000,
0xbf7b3e48,0xbe48bf7b,0xbec4bf6d,0x3f6dbec4,0x3f55bf0e,0x3f0e3f55,0x3f353f35,0xbf353f35,0xbf0e3f55,0xbf55bf0e,0xbf6dbec4,0x3ec4bf6d,0x3e48bf7b,0x3f7b3e48,0x3f800000,0x3f80,
0xbec4bf6d,0x3f6dbec4,0x3f353f35,0xbf353f35,0xbf6dbec4,0x3ec4bf6d,0x3f800000,0x3f80,0xbf6d3ec4,0xbec4bf6d,0x3f35bf35,0x3f353f35,0xbec43f6d,0xbf6dbec4,0xbf80,0x3f800000,
0xbe48bf7b,0x3f7bbe48,0x3ec43f6d,0xbf6d3ec4,0xbf0ebf55,0x3f55bf0e,0x3f353f35,0xbf353f35,0xbf55bf0e,0x3f0ebf55,0x3f6d3ec4,0xbec43f6d,0xbf7bbe48,0x3e48bf7b,0x3f800000,0x3f80,
0x3f6dbec4,0x3ec43f6d,0xbf35bf35,0x3f35bf35,0xbec43f6d,0xbf6dbec4,0x3f800000,0x3f80,0xbec4bf6d,0x3f6dbec4,0xbf353f35,0xbf35bf35,0x3f6d3ec4,0xbec43f6d,0xbf80,0x3f800000,
0x3f7bbe48,0x3e483f7b,0xbec4bf6d,0x3f6dbec4,0xbf553f0e,0xbf0ebf55,0x3f353f35,0xbf353f35,0x3f0ebf55,0x3f553f0e,0xbf6dbec4,0x3ec4bf6d,0xbe483f7b,0xbf7bbe48,0x3f800000,0x3f80,
0x3ec43f6d,0xbf6d3ec4,0x3f353f35,0xbf353f35,0x3f6d3ec4,0xbec43f6d,0x3f800000,0x3f80,0x3f6dbec4,0x3ec43f6d,0x3f35bf35,0x3f353f35,0x3ec4bf6d,0x3f6d3ec4,0xbf80,0x3f800000,
0x3e483f7b,0xbf7b3e48,0x3ec43f6d,0xbf6d3ec4,0x3f0e3f55,0xbf553f0e,0x3f353f35,0xbf353f35,0x3f553f0e,0xbf0e3f55,0x3f6d3ec4,0xbec43f6d,0x3f7b3e48,0xbe483f7b,0x3f800000,0x3f80,
0x3f6dbec4,0x3ec43f6d,0x3f353f35,0xbf353f35,0xbec43f6d,0xbf6dbec4,0xbf800000,0xbf80,0xbec4bf6d,0x3f6dbec4,0x3f35bf35,0x3f353f35,0x3f6d3ec4,0xbec43f6d,0x3f80,0xbf800000,
0x3e483f7b,0xbf7b3e48,0xbf6d3ec4,0xbec4bf6d,0xbf0ebf55,0x3f55bf0e,0x3f35bf35,0x3f353f35,0x3f553f0e,0xbf0e3f55,0xbec43f6d,0xbf6dbec4,0xbf7bbe48,0x3e48bf7b,0xbf80,0x3f800000,
0x3ec43f6d,0xbf6d3ec4,0xbf35bf35,0x3f35bf35,0x3f6d3ec4,0xbec43f6d,0xbf800000,0xbf80,0x3f6dbec4,0x3ec43f6d,0xbf353f35,0xbf35bf35,0x3ec4bf6d,0x3f6d3ec4,0x3f80,0xbf800000,
0xbf7b3e48,0xbe48bf7b,0x3f6dbec4,0x3ec43f6d,0xbf553f0e,0xbf0ebf55,0x3f35bf35,0x3f353f35,0xbf0e3f55,0xbf55bf0e,0x3ec4bf6d,0x3f6d3ec4,0xbe483f7b,0xbf7bbe48,0xbf80,0x3f800000,
0xbf6d3ec4,0xbec4bf6d,0x3f353f35,0xbf353f35,0x3ec4bf6d,0x3f6d3ec4,0xbf800000,0xbf80,0x3ec43f6d,0xbf6d3ec4,0x3f35bf35,0x3f353f35,0xbf6dbec4,0x3ec4bf6d,0x3f80,0xbf800000,
0xbe48bf7b,0x3f7bbe48,0xbf6d3ec4,0xbec4bf6d,0x3f0e3f55,0xbf553f0e,0x3f35bf35,0x3f353f35,0xbf55bf0e,0x3f0ebf55,0xbec43f6d,0xbf6dbec4,0x3f7b3e48,0xbe483f7b,0xbf80,0x3f800000,
0xbec4bf6d,0x3f6dbec4,0xbf35bf35,0x3f35bf35,0xbf6dbec4,0x3ec4bf6d,0xbf800000,0xbf80,0xbf6d3ec4,0xbec4bf6d,0xbf353f35,0xbf35bf35,0xbec43f6d,0xbf6dbec4,0x3f80,0xbf800000,
0x3f7bbe48,0x3e483f7b,0x3f6dbec4,0x3ec43f6d,0x3f55bf0e,0x3f0e3f55,0x3f35bf35,0x3f353f35,0x3f0ebf55,0x3f553f0e,0x3ec4bf6d,0x3f6d3ec4,0x3e48bf7b,0x3f7b3e48,0xbf80,0x3f800000,
0x3f800000,0x3f800000,0x0,0x0,0x3f800000,0x3f800000,0x0,0x0,0x3f800000,0x3f800000,0x0,0x0,0x3f800000,0x3f800000,0x0,0x0,
0x3f800000,0x3f7ffb11,0x0,0x3c490e90,0x3f7fec43,0x3f7fd397,0x3cc90ab0,0x3d16c32c,0x3f7fb10f,0x3f7f84ab,0x3d48fb30,0x3d7b2b74,0x3f7f4e6d,0x3f7f0e58,0x3d96a905,0x3dafb680,
0x3f800000,0x3f7ec46d,0x0,0x3dc8bd36,0x3f7b14be,0x3f74fa0b,0x3e47c5c2,0x3e94a031,0x3f6c835e,0x3f61c598,0x3ec3ef15,0x3ef15aea,0x3f54db31,0x3f45e403,0x3f0e39da,0x3f226799,
0x3f800000,0x3f7e70b0,0x0,0x3de1bc2e,0x3f79c79d,0x3f721352,0x3e605c13,0x3ea68f12,0x3f676bd8,0x3f59f26a,0x3edae880,0x3f064b82,0x3f49d112,0x3f373a23,0x3f1d7fd1,0x3f32c8c9,
0x3f800000,0x3f7b14be,0x0,0x3e47c5c2,0x3f6c835e,0x3f54db31,0x3ec3ef15,0x3f0e39da,0x3f3504f3,0x3f0e39da,0x3f3504f3,0x3f54db31,0x3ec3ef15,0x3e47c5c2,0x3f6c835e,0x3f7b14be,
0x3f800000,0x3f7a7302,0x0,0x3e541501,0x3f6a09a7,0x3f4f7a1f,0x3ecf7bca,0x3f15f6d9,0x3f2beb4a,0x3f00e7e4,0x3f3daef9,0x3f5d2d53,0x3ea09ae5,0x3de1bc2e,0x3f731447,0x3f7e70b0,
0x3f800000,0x3f74fa0b,0x0,0x3e94a031,0x3f54db31,0x3f226799,0x3f0e39da,0x3f45e403,0x3ec3ef15,0x3dc8bd36,0x3f6c835e,0x3f7ec46d,0xbe47c5c2,0xbef15aea,0x3f7b14be,0x3f61c598,
0x3f800000,0x3f740bdd,0x0,0x3e9aa086,0x3f514d3d,0x3f1b02c6,0x3f13682a,0x3f4bbbf8,0x3eac7cd4,0x3d16c32c,0x3f710908,0x3f7fd397,0xbe888e93,0xbf0b9a6b,0x3f76ba07,0x3f5695e5,
0x3f800000,0x3f7fec43,0x0,0x3cc90ab0,0x3f7fb10f,0x3f7f4e6d,0x3d48fb30,0x3d96a905,0x3f7ec46d,0x3f7e1324,0x3dc8bd36,0x3dfab273,0x3f7d3aac,0x3f7c3b28,0x3e164083,0x3e2f10a2,
0x3f800000,0x3f7fd397,0x0,0x3d16c32c,0x3f7f4e6d,0x3f7e70b0,0x3d96a905,0x3de1bc2e,0x3f7d3aac,0x3f7baccd,0x3e164083,0x3e3b6ecf,0x3f79c79d,0x3f778bc5,0x3e605c13,0x3e827dc0,
0x3f800000,0x3f7e1324,0x0,0x3dfab273,0x3f7853f8,0x3f6ed89e,0x3e78cfcc,0x3eb8442a,0x3f61c598,0x3f514d3d,0x3ef15aea,0x3f13682a,0x3f3daef9,0x3f273656,0x3f2beb4a,0x3f41d870,
0x3f800000,0x3f7dabcc,0x0,0x3e09cf86,0x3f76ba07,0x3f6b4b0c,0x3e888e93,0x3ec9b953,0x3f5b941a,0x3f47de65,0x3f039c3d,0x3f1ff6cb,0x3f3085bb,0x3f15f6d9,0x3f396842,0x3f4f7a1f,
0x3f800000,0x3f79c79d,0x0,0x3e605c13,0x3f676bd8,0x3f49d112,0x3edae880,0x3f1d7fd1,0x3f226799,0x3ee63375,0x3f45e403,0x3f64aa59,0x3e78cfcc,0x3cc90ab0,0x3f7853f8,0x3f7fec43,
0x3f800000,0x3f791298,0x0,0x3e6c9a7f,0x3f64aa59,0x3f43e200,0x3ee63375,0x3f24d225,0x3f187fc0,0x3ec9b953,0x3f4d9f02,0x3f6b4b0c,0x3e2f10a2,0xbd7b2b74,0x3f7c3b28,0x3f7f84ab,
0x3f800000,0x3f731447,0x0,0x3ea09ae5,0x3f4d9f02,0x3f13682a,0x3f187fc0,0x3f514d3d,0x3e94a031,0xbcc90ab0,0x3f74fa0b,0x3f7fec43,0xbeac7cd4,0xbf1d7fd1,0x3f710908,0x3f49d112,
0x3f800000,0x3f721352,0x0,0x3ea68f12,0x3f49d112,0x3f0b9a6b,0x3f1d7fd1,0x3f5695e5,0x3e78cfcc,0xbdafb680,0x3f7853f8,0x3f7f0e58,0xbecf7bca,0xbf2e3bde,0x3f6a09a7,0x3f3b8f3b,
0x3f800000,0x3f7fb10f,0x0,0x3d48fb30,0x3f7ec46d,0x3f7d3aac,0x3dc8bd36,0x3e164083,0x3f7b14be,0x3f7853f8,0x3e47c5c2,0x3e78cfcc,0x3f74fa0b,0x3f710908,0x3e94a031,0x3eac7cd4,
0x3f800000,0x3f7f84ab,0x0,0x3d7b2b74,0x3f7e1324,0x3f7baccd,0x3dfab273,0x3e3b6ecf,0x3f7853f8,0x3f740bdd,0x3e78cfcc,0x3e9aa086,0x3f6ed89e,0x3f68bf3c,0x3eb8442a,0x3ed53641,
0x3f800000,0x3f7d3aac,0x0,0x3e164083,0x3f74fa0b,0x3f676bd8,0x3e94a031,0x3edae880,0x3f54db31,0x3f3daef9,0x3f0e39da,0x3f2beb4a,0x3f226799,0x3f039c3d,0x3f45e403,0x3f5b941a,
0x3f800000,0x3f7cbfc9,0x0,0x3e22abb6,0x3f731447,0x3f633c5a,0x3ea09ae5,0x3eebcbbb,0x3f4d9f02,0x3f32c8c9,0x3f187fc0,0x3f373a23,0x3f13682a,0x3ee0924f,0x3f514d3d,0x3f660f88,
0x3f800000,0x3f7853f8,0x0,0x3e78cfcc,0x3f61c598,0x3f3daef9,0x3ef15aea,0x3f2beb4a,0x3f0e39da,0x3eac7cd4,0x3f54db31,0x3f710908,0x3dc8bd36,0xbe164083,0x3f7ec46d,0x3f7d3aac,
0x3f800000,0x3f778bc5,0x0,0x3e827dc0,0x3f5ebe05,0x3f373a23,0x3efc5d27,0x3f32c8c9,0x3f039c3d,0x3e8e9a22,0x3f5b941a,0x3f75dec6,0x3cc90ab0,0xbe6c9a7f,0x3f7fec43,0x3f791298,
0x3f800000,0x3f710908,0x0,0x3eac7cd4,0x3f45e403,0x3f039c3d,0x3f226799,0x3f5b941a,0x3e47c5c2,0xbe164083,0x3f7b14be,0x3f7d3aac,0xbef15aea,0xbf3daef9,0x3f61c598,0x3f2beb4a,
0x3f800000,0x3f6ff573,0x0,0x3eb263ef,0x3f41d870,0x3ef6e0cb,0x3f273656,0x3f604621,0x3e164083,0xbe541501,0x3f7d3aac,0x3f7a7302,0xbf08f59b,0xbf4bbbf8,0x3f584853,0x3f1b02c6,
0x3f800000,0x3f7f4e6d,0x0,0x3d96a905,0x3f7d3aac,0x3f79c79d,0x3e164083,0x3e605c13,0x3f74fa0b,0x3f6ed89e,0x3e94a031,0x3eb8442a,0x3f676bd8,0x3f5ebe05,0x3edae880,0x3efc5d27,
0x3f800000,0x3f7f0e58,0x0,0x3dafb680,0x3f7c3b28,0x3f778bc5,0x3e2f10a2,0x3e827dc0,0x3f710908,0x3f68bf3c,0x3eac7cd4,0x3ed53641,0x3f5ebe05,0x3f531849,0x3efc5d27,0x3f10d3cd,
0x3f800000,0x3f7c3b28,0x0,0x3e2f10a2,0x3f710908,0x3f5ebe05,0x3eac7cd4,0x3efc5d27,0x3f45e403,0x3f273656,0x3f226799,0x3f41d870,0x3f039c3d,0x3eb8442a,0x3f5b941a,0x3f6ed89e,
0x3f800000,0x3f7baccd,0x0,0x3e3b6ecf,0x3f6ed89e,0x3f59f26a,0x3eb8442a,0x3f064b82,0x3f3daef9,0x3f1b02c6,0x3f2beb4a,0x3f4bbbf8,0x3ee63375,0x3e8e9a22,0x3f64aa59,0x3f75dec6,
0x3f800000,0x3f76ba07,0x0,0x3e888e93,0x3f5b941a,0x3f3085bb,0x3f039c3d,0x3f396842,0x3ef15aea,0x3e605c13,0x3f61c598,0x3f79c79d,0xbd48fb30,0xbea09ae5,0x3f7fb10f,0x3f731447,
0x3f800000,0x3f75dec6,0x0,0x3e8e9a22,0x3f584853,0x3f299415,0x3f08f59b,0x3f3fc767,0x3edae880,0x3e22abb6,0x3f676bd8,0x3f7cbfc9,0xbdfab273,0xbec9b953,0x3f7e1324,0x3f6b4b0c,
0x3f800000,0x3f6ed89e,0x0,0x3eb8442a,0x3f3daef9,0x3ee63375,0x3f2beb4a,0x3f64aa59,0x3dc8bd36,0xbe888e93,0x3f7ec46d,0x3f76ba07,0xbf187fc0,0xbf584853,0x3f4d9f02,0x3f08f59b,
0x3f800000,0x3f6db293,0x0,0x3ebe1d4a,0x3f396842,0x3ed53641,0x3f3085bb,0x3f68bf3c,0x3d48fb30,0xbea68f12,0x3f7fb10f,0x3f721352,0xbf273656,0xbf633c5a,0x3f41d870,0x3eebcbbb,
0x3f800000,0x3f7b14be,0x3f6c835e,0x3f54db31,0x3f800000,0x3f7b14be,0x3f6c835e,0x3f54db31,0x3f800000,0x3f7b14be,0x3f6c835e,0x3f54db31,0x3f800000,0x3f7b14be,0x3f6c835e,0x3f54db31,
0x3f7ec46d,0x3f74fa0b,0x3f61c598,0x3f45e403,0x3f7ec46d,0x3f74fa0b,0x3f61c598,0x3f45e403,0x3f7ec46d,0x3f74fa0b,0x3f61c598,0x3f45e403,0x3f7ec46d,0x3f74fa0b,0x3f61c598,0x3f45e403,
0x3f3504f3,0x3f0e39da,0x3ec3ef15,0x3e47c5c2,0x3f3504f3,0x3f0e39da,0x3ec3ef15,0x3e47c5c2,0x3f3504f3,0x3f0e39da,0x3ec3ef15,0x3e47c5c2,0x3f3504f3,0x3f0e39da,0x3ec3ef15,0x3e47c5c2,
0x3f226799,0x3ef15aea,0x3e94a031,0x3dc8bd36,0x3f226799,0x3ef15aea,0x3e94a031,0x3dc8bd36,0x3f226799,0x3ef15aea,0x3e94a031,0x3dc8bd36,0x3f226799,0x3ef15aea,0x3e94a031,0x3dc8bd36,
0x0,0xbe47c5c2,0xbec3ef15,0xbf0e39da,0x0,0xbe47c5c2,0xbec3ef15,0xbf0e39da,0x0,0xbe47c5c2,0xbec3ef15,0xbf0e39da,0x0,0xbe47c5c2,0xbec3ef15,0xbf0e39da,
0xbdc8bd36,0xbe94a031,0xbef15aea,0xbf226799,0xbdc8bd36,0xbe94a031,0xbef15aea,0xbf226799,0xbdc8bd36,0xbe94a031,0xbef15aea,0xbf226799,0xbdc8bd36,0xbe94a031,0xbef15aea,0xbf226799,
0xbf3504f3,0xbf54db31,0xbf6c835e,0xbf7b14be,0xbf3504f3,0xbf54db31,0xbf6c835e,0xbf7b14be,0xbf3504f3,0xbf54db31,0xbf6c835e,0xbf7b14be,0xbf3504f3,0xbf54db31,0xbf6c835e,0xbf7b14be,
0xbf45e403,0xbf61c598,0xbf74fa0b,0xbf7ec46d,0xbf45e403,0xbf61c598,0xbf74fa0b,0xbf7ec46d,0xbf45e403,0xbf61c598,0xbf74fa0b,0xbf7ec46d,0xbf45e403,0xbf61c598,0xbf74fa0b,0xbf7ec46d,
0x0,0x3e47c5c2,0x3ec3ef15,0x3f0e39da,0x0,0x3e47c5c2,0x3ec3ef15,0x3f0e39da,0x0,0x3e47c5c2,0x3ec3ef15,0x3f0e39da,0x0,0x3e47c5c2,0x3ec3ef15,0x3f0e39da,
0x3dc8bd36,0x3e94a031,0x3ef15aea,0x3f226799,0x3dc8bd36,0x3e94a031,0x3ef15aea,0x3f226799,0x3dc8bd36,0x3e94a031,0x3ef15aea,0x3f226799,0x3dc8bd36,0x3e94a031,0x3ef15aea,0x3f226799,
0x3f3504f3,0x3f54db31,0x3f6c835e,0x3f7b14be,0x3f3504f3,0x3f54db31,0x3f6c835e,0x3f7b14be,0x3f3504f3,0x3f54db31,0x3f6c835e,0x3f7b14be,0x3f3504f3,0x3f54db31,0x3f6c835e,0x3f7b14be,
0x3f45e403,0x3f61c598,0x3f74fa0b,0x3f7ec46d,0x3f45e403,0x3f61c598,0x3f74fa0b,0x3f7ec46d,0x3f45e403,0x3f61c598,0x3f74fa0b,0x3f7ec46d,0x3f45e403,0x3f61c598,0x3f74fa0b,0x3f7ec46d,
0x3f800000,0x3f7b14be,0x3f6c835e,0x3f54db31,0x3f800000,0x3f7b14be,0x3f6c835e,0x3f54db31,0x3f800000,0x3f7b14be,0x3f6c835e,0x3f54db31,0x3f800000,0x3f7b14be,0x3f6c835e,0x3f54db31,
0x3f7ec46d,0x3f74fa0b,0x3f61c598,0x3f45e403,0x3f7ec46d,0x3f74fa0b,0x3f61c598,0x3f45e403,0x3f7ec46d,0x3f74fa0b,0x3f61c598,0x3f45e403,0x3f7ec46d,0x3f74fa0b,0x3f61c598,0x3f45e403,
0x3f3504f3,0x3f0e39da,0x3ec3ef15,0x3e47c5c2,0x3f3504f3,0x3f0e39da,0x3ec3ef15,0x3e47c5c2,0x3f3504f3,0x3f0e39da,0x3ec3ef15,0x3e47c5c2,0x3f3504f3,0x3f0e39da,0x3ec3ef15,0x3e47c5c2,
0x3f226799,0x3ef15aea,0x3e94a031,0x3dc8bd36,0x3f226799,0x3ef15aea,0x3e94a031,0x3dc8bd36,0x3f226799,0x3ef15aea,0x3e94a031,0x3dc8bd36,0x3f226799,0x3ef15aea,0x3e94a031,0x3dc8bd36,
0x3f803f80,0xbf803f80,0x3f80,0x3f80,0x3f803f80,0xbf803f80,0x0,0x0,0x3f803f80,0xbf803f80,0x0,0x0,0x3f803f80,0xbf803f80,0x0,0x0,
0x3f6d3f80,0xbf6d3f80,0xbec4bf80,0x3ec4bf80,0x3ec43f35,0xbec43f35,0xbf6dbf35,0x3f6dbf35,0xbec40000,0x3ec40000,0xbf6dbf80,0x3f6dbf80,0xbf6dbf35,0x3f6dbf35,0xbec4bf35,0x3ec4bf35,
0x3f353f80,0xbf353f80,0xbf353f80,0x3f353f80,0xbf350000,0x3f350000,0xbf35bf80,0x3f35bf80,0xbf35bf80,0x3f35bf80,0x3f350000,0xbf350000,0x3f350000,0xbf350000,0x3f353f80,0xbf353f80,
0x3ec43f80,0xbec43f80,0xbf6dbf80,0x3f6dbf80,0xbf6dbf35,0x3f6dbf35,0x3ec4bf35,0xbec4bf35,0x3f6d0000,0xbf6d0000,0x3ec43f80,0xbec43f80,0xbec43f35,0x3ec43f35,0xbf6dbf35,0x3f6dbf35,
0x3f80,0x3f80,0xbf803f80,0x3f803f80,0xbf80,0xbf80,0x3f800000,0xbf800000,0x3f80,0x3f80,0xbf800000,0x3f800000,0xbf80,0xbf80,0x3f800000,0xbf800000,
0xbec43f80,0x3ec43f80,0xbf6dbf80,0x3f6dbf80,0x3f6dbf35,0xbf6dbf35,0x3ec43f35,0xbec43f35,0xbf6d0000,0x3f6d0000,0x3ec4bf80,0xbec4bf80,0x3ec43f35,0xbec43f35,0xbf6d3f35,0x3f6d3f35,
0xbf353f80,0x3f353f80,0xbf353f80,0x3f353f80,0x3f350000,0xbf350000,0xbf353f80,0x3f353f80,0x3f35bf80,0xbf35bf80,0x3f350000,0xbf350000,0xbf350000,0x3f350000,0x3f35bf80,0xbf35bf80,
0xbf6d3f80,0x3f6d3f80,0xbec4bf80,0x3ec4bf80,0xbec43f35,0x3ec43f35,0xbf6d3f35,0x3f6d3f35,0x3ec40000,0xbec40000,0xbf6d3f80,0x3f6d3f80,0x3f6dbf35,0xbf6dbf35,0xbec43f35,0x3ec43f35,
};

constexpr uint32_t TAGM = 0x10001u, TAG1 = 1u, TAG2 = 0u, TAG3 = 0x10000u;
struct Scratch {
  __nv_bfloat16 hn[2048 * 512];
  uint32_t G[16 * 8 * 128 * 32];
  unsigned cnt[32 * 32];
};
__device__ __align__(1024) Scratch g_scr;
#define TS(i)
#define TW(i)
#define TSX(i)

__device__ __forceinline__ uint32_t s2u(const void* p) { return (uint32_t)__cvta_generic_to_shared(p); }
__device__ __forceinline__ void mbar_init(uint32_t b, uint32_t c) { asm volatile("mbarrier.init.shared::cta.b64 [%0], %1;" ::"r"(b), "r"(c)); }
__device__ __forceinline__ void mbar_expect(uint32_t b, uint32_t bytes) { asm volatile("mbarrier.arrive.expect_tx.shared::cta.b64 _, [%0], %1;" ::"r"(b), "r"(bytes) : "memory"); }
__device__ __forceinline__ void mbar_arrive(uint32_t b) { asm volatile("mbarrier.arrive.shared::cta.b64 _, [%0];" ::"r"(b) : "memory"); }
__device__ __forceinline__ void mbar_wait(uint32_t b, uint32_t ph) {
  uint32_t ok = 0;
#pragma unroll 1
  for (int it = 0; it < (1 << 20); it++) {
    asm volatile("{.reg .pred p; mbarrier.try_wait.parity.shared::cta.b64 p, [%1], %2; selp.u32 %0,1,0,p;}" : "=r"(ok) : "r"(b), "r"(ph) : "memory");
    if (ok) break;
  }
}
__device__ __forceinline__ uint32_t peer(uint32_t a) { uint32_t r; asm("mapa.shared::cluster.u32 %0, %1, %2;" : "=r"(r) : "r"(a), "r"((blockIdx.x & 1) ^ 1)); return r; }
__device__ __forceinline__ void rem_arrive(uint32_t b) { asm volatile("mbarrier.arrive.relaxed.cluster.shared::cluster.b64 _, [%0];" ::"r"(b) : "memory"); }
__device__ __forceinline__ void bar_sync(int id, int n) { asm volatile("bar.sync %0, %1;" ::"r"(id), "r"(n) : "memory"); }
__device__ __forceinline__ unsigned ld_acq(const unsigned* p) { unsigned v; asm volatile("ld.acquire.gpu.global.u32 %0, [%1];" : "=r"(v) : "l"(p) : "memory"); return v; }
__device__ __forceinline__ void red_rel(unsigned* p) { asm volatile("red.release.gpu.global.add.u32 [%0], 1;" ::"l"(p) : "memory"); }
__device__ __forceinline__ void poll(const unsigned* p, unsigned target) {
#pragma unroll 1
  for (int it = 0; it < (1 << 20); it++) if ((int)(ld_acq(p) - target) >= 0) break;
}
__device__ __forceinline__ void fence_async_g() { asm volatile("fence.proxy.async.global;" ::: "memory"); }
__device__ __forceinline__ void fence_async_s() { asm volatile("fence.proxy.async.shared::cta;" ::: "memory"); }
__device__ __forceinline__ uint32_t pk(float lo, float hi) { uint32_t r; asm("cvt.rn.bf16x2.f32 %0, %1, %2;" : "=r"(r) : "f"(hi), "f"(lo)); return r; }
__device__ __forceinline__ uint32_t add2(uint32_t a, uint32_t b) { uint32_t r; asm("add.rn.bf16x2 %0, %1, %2;" : "=r"(r) : "r"(a), "r"(b)); return r; }
__device__ __forceinline__ float blo(uint32_t v) { return __uint_as_float(v << 16); }
__device__ __forceinline__ float bhi(uint32_t v) { return __uint_as_float(v & 0xffff0000u); }
__device__ __forceinline__ float rbf(float v) { return __bfloat162float(__float2bfloat16_rn(v)); }
__device__ __forceinline__ void mma(float (&c)[4], uint32_t a0, uint32_t a1, uint32_t a2, uint32_t a3, uint32_t b0, uint32_t b1) {
  asm("mma.sync.aligned.m16n8k16.row.col.f32.bf16.bf16.f32 {%0,%1,%2,%3}, {%4,%5,%6,%7}, {%8,%9}, {%0,%1,%2,%3};"
               : "+f"(c[0]), "+f"(c[1]), "+f"(c[2]), "+f"(c[3]) : "r"(a0), "r"(a1), "r"(a2), "r"(a3), "r"(b0), "r"(b1));
}
__device__ __forceinline__ void mma(float (&c)[4], const uint4& a, uint32_t b0, uint32_t b1) { mma(c, a.x, a.y, a.z, a.w, b0, b1); }
__device__ __forceinline__ void st4(uint32_t* p, uint32_t a, uint32_t b, uint32_t c, uint32_t d, uint32_t tag) {
  asm volatile("{.reg .b128 v; .reg .b64 l, h; mov.b64 l, {%0,%1}; mov.b64 h, {%2,%3}; mov.b128 v, {l, h}; st.relaxed.gpu.global.b128 [%4], v;}"
               ::"r"((a & ~TAGM) | tag), "r"(b), "r"(c), "r"(d), "l"(p) : "memory");
}
__device__ __forceinline__ void ld4(uint32_t (&z)[4][4], const uint32_t* p, int stride) {
#pragma unroll
  for (int u = 0; u < 4; u++)
    asm volatile("{.reg .b128 v; .reg .b64 l, h; ld.relaxed.gpu.global.b128 v, [%4]; mov.b128 {l, h}, v; mov.b64 {%0,%1}, l; mov.b64 {%2,%3}, h;}"
                 : "=r"(z[u][0]), "=r"(z[u][1]), "=r"(z[u][2]), "=r"(z[u][3]) : "l"(p + u * stride) : "memory");
}
__device__ __forceinline__ bool stale(const uint32_t (&z)[4][4], uint32_t tag) {
  return __any_sync(~0u, ((z[0][0] ^ tag) | (z[1][0] ^ tag) | (z[2][0] ^ tag) | (z[3][0] ^ tag)) & TAGM);
}
__device__ __forceinline__ void poll_ld(uint32_t (&z)[4][4], const uint32_t* p, int stride, uint32_t tag) {
#pragma unroll 1
  for (int it = 0; it < (1 << 18); it++) {
    ld4(z, p, stride);
    if (!stale(z, tag)) break;
  }
}
__device__ __forceinline__ void delay(long long t0, int n) { while (clock64() - t0 < n) {} }
__device__ __forceinline__ float4 asf(const uint4& a) { return make_float4(__uint_as_float(a.x), __uint_as_float(a.y), __uint_as_float(a.z), __uint_as_float(a.w)); }
__device__ __forceinline__ uint4 neg4(const uint4& a) { return make_uint4(a.x ^ 0x80008000u, a.y ^ 0x80008000u, a.z ^ 0x80008000u, a.w ^ 0x80008000u); }
__device__ __forceinline__ void tma3(uint32_t dst, const CUtensorMap* m, int c0, int c1, int c2, uint32_t bar) {
  asm volatile("cp.async.bulk.tensor.3d.shared::cluster.global.mbarrier::complete_tx::bytes [%0], [%1, {%3, %4, %5}], [%2];"
               ::"r"(dst), "l"(m), "r"(bar), "r"(c0), "r"(c1), "r"(c2) : "memory");
}
__device__ __forceinline__ void tma2(uint32_t dst, const CUtensorMap* m, int c0, int c1, uint32_t bar) {
  asm volatile("cp.async.bulk.tensor.2d.shared::cluster.global.mbarrier::complete_tx::bytes [%0], [%1, {%3, %4}], [%2];"
               ::"r"(dst), "l"(m), "r"(bar), "r"(c0), "r"(c1) : "memory");
}
__device__ __forceinline__ uint64_t mkdesc(uint32_t addr, uint32_t lbo, uint32_t sbo, uint32_t swz) {
  return (uint64_t)((addr & 0x3FFFF) >> 4) | ((uint64_t)(lbo >> 4) << 16) | ((uint64_t)(sbo >> 4) << 32) | ((uint64_t)swz << 62);
}
__device__ __forceinline__ void wg_fence() { asm volatile("wgmma.fence.sync.aligned;" ::: "memory"); }
__device__ __forceinline__ void wg_commit() { asm volatile("wgmma.commit_group.sync.aligned;" ::: "memory"); }
template <int N> __device__ __forceinline__ void wg_wait() { asm volatile("wgmma.wait_group.sync.aligned %0;" ::"n"(N) : "memory"); }
template <int N> __device__ __forceinline__ void keep(float (&d)[N]) {
#pragma unroll
  for (int i = 0; i < N; i++) asm volatile("" : "+f"(d[i])::"memory");
}
__device__ __forceinline__ void wgmma_ss_n224(float (&d)[112], uint64_t da, uint64_t db, int sc) {
  asm volatile("{.reg .pred p; setp.ne.b32 p, %114, 0;\n"
    "wgmma.mma_async.sync.aligned.m64n224k16.f32.bf16.bf16 {%0, %1, %2, %3, %4, %5, %6, %7, %8, %9, %10, %11, %12, %13, %14, %15, %16, %17, %18, %19, %20, %21, %22, %23, %24, %25, %26, %27, %28, %29, %30, %31, %32, %33, %34, %35, %36, %37, %38, %39, %40, %41, %42, %43, %44, %45, %46, %47, %48, %49, %50, %51, %52, %53, %54, %55, %56, %57, %58, %59, %60, %61, %62, %63, %64, %65, %66, %67, %68, %69, %70, %71, %72, %73, %74, %75, %76, %77, %78, %79, %80, %81, %82, %83, %84, %85, %86, %87, %88, %89, %90, %91, %92, %93, %94, %95, %96, %97, %98, %99, %100, %101, %102, %103, %104, %105, %106, %107, %108, %109, %110, %111}, %112, %113, p, 1, 1, 0, 1;}\n"
    : "+f"(d[0]), "+f"(d[1]), "+f"(d[2]), "+f"(d[3]), "+f"(d[4]), "+f"(d[5]), "+f"(d[6]), "+f"(d[7]), "+f"(d[8]), "+f"(d[9]), "+f"(d[10]), "+f"(d[11]), "+f"(d[12]), "+f"(d[13]), "+f"(d[14]), "+f"(d[15]), "+f"(d[16]), "+f"(d[17]), "+f"(d[18]), "+f"(d[19]), "+f"(d[20]), "+f"(d[21]), "+f"(d[22]), "+f"(d[23]), "+f"(d[24]), "+f"(d[25]), "+f"(d[26]), "+f"(d[27]), "+f"(d[28]), "+f"(d[29]), "+f"(d[30]), "+f"(d[31]), "+f"(d[32]), "+f"(d[33]), "+f"(d[34]), "+f"(d[35]), "+f"(d[36]), "+f"(d[37]), "+f"(d[38]), "+f"(d[39]), "+f"(d[40]), "+f"(d[41]), "+f"(d[42]), "+f"(d[43]), "+f"(d[44]), "+f"(d[45]), "+f"(d[46]), "+f"(d[47]), "+f"(d[48]), "+f"(d[49]), "+f"(d[50]), "+f"(d[51]), "+f"(d[52]), "+f"(d[53]), "+f"(d[54]), "+f"(d[55]), "+f"(d[56]), "+f"(d[57]), "+f"(d[58]), "+f"(d[59]), "+f"(d[60]), "+f"(d[61]), "+f"(d[62]), "+f"(d[63]), "+f"(d[64]), "+f"(d[65]), "+f"(d[66]), "+f"(d[67]), "+f"(d[68]), "+f"(d[69]), "+f"(d[70]), "+f"(d[71]), "+f"(d[72]), "+f"(d[73]), "+f"(d[74]), "+f"(d[75]), "+f"(d[76]), "+f"(d[77]), "+f"(d[78]), "+f"(d[79]), "+f"(d[80]), "+f"(d[81]), "+f"(d[82]), "+f"(d[83]), "+f"(d[84]), "+f"(d[85]), "+f"(d[86]), "+f"(d[87]), "+f"(d[88]), "+f"(d[89]), "+f"(d[90]), "+f"(d[91]), "+f"(d[92]), "+f"(d[93]), "+f"(d[94]), "+f"(d[95]), "+f"(d[96]), "+f"(d[97]), "+f"(d[98]), "+f"(d[99]), "+f"(d[100]), "+f"(d[101]), "+f"(d[102]), "+f"(d[103]), "+f"(d[104]), "+f"(d[105]), "+f"(d[106]), "+f"(d[107]), "+f"(d[108]), "+f"(d[109]), "+f"(d[110]), "+f"(d[111]) : "l"(da), "l"(db), "r"(sc));
}
__device__ __forceinline__ void wgmma_rs_n128(float (&d)[64], uint32_t a0, uint32_t a1, uint32_t a2, uint32_t a3, uint64_t db, int sc) {
  asm volatile("{.reg .pred p; setp.ne.b32 p, %69, 0;\n"
    "wgmma.mma_async.sync.aligned.m64n128k16.f32.bf16.bf16 {%0, %1, %2, %3, %4, %5, %6, %7, %8, %9, %10, %11, %12, %13, %14, %15, %16, %17, %18, %19, %20, %21, %22, %23, %24, %25, %26, %27, %28, %29, %30, %31, %32, %33, %34, %35, %36, %37, %38, %39, %40, %41, %42, %43, %44, %45, %46, %47, %48, %49, %50, %51, %52, %53, %54, %55, %56, %57, %58, %59, %60, %61, %62, %63}, {%64, %65, %66, %67}, %68, p, 1, 1, 1;}\n"
    : "+f"(d[0]), "+f"(d[1]), "+f"(d[2]), "+f"(d[3]), "+f"(d[4]), "+f"(d[5]), "+f"(d[6]), "+f"(d[7]), "+f"(d[8]), "+f"(d[9]), "+f"(d[10]), "+f"(d[11]), "+f"(d[12]), "+f"(d[13]), "+f"(d[14]), "+f"(d[15]), "+f"(d[16]), "+f"(d[17]), "+f"(d[18]), "+f"(d[19]), "+f"(d[20]), "+f"(d[21]), "+f"(d[22]), "+f"(d[23]), "+f"(d[24]), "+f"(d[25]), "+f"(d[26]), "+f"(d[27]), "+f"(d[28]), "+f"(d[29]), "+f"(d[30]), "+f"(d[31]), "+f"(d[32]), "+f"(d[33]), "+f"(d[34]), "+f"(d[35]), "+f"(d[36]), "+f"(d[37]), "+f"(d[38]), "+f"(d[39]), "+f"(d[40]), "+f"(d[41]), "+f"(d[42]), "+f"(d[43]), "+f"(d[44]), "+f"(d[45]), "+f"(d[46]), "+f"(d[47]), "+f"(d[48]), "+f"(d[49]), "+f"(d[50]), "+f"(d[51]), "+f"(d[52]), "+f"(d[53]), "+f"(d[54]), "+f"(d[55]), "+f"(d[56]), "+f"(d[57]), "+f"(d[58]), "+f"(d[59]), "+f"(d[60]), "+f"(d[61]), "+f"(d[62]), "+f"(d[63]) : "r"(a0), "r"(a1), "r"(a2), "r"(a3), "l"(db), "r"(sc));
}
__device__ __forceinline__ void wgmma_rs_n64(float (&d)[32], uint32_t a0, uint32_t a1, uint32_t a2, uint32_t a3, uint64_t db, int sc) {
  asm volatile("{.reg .pred p; setp.ne.b32 p, %37, 0;\n"
    "wgmma.mma_async.sync.aligned.m64n64k16.f32.bf16.bf16 {%0, %1, %2, %3, %4, %5, %6, %7, %8, %9, %10, %11, %12, %13, %14, %15, %16, %17, %18, %19, %20, %21, %22, %23, %24, %25, %26, %27, %28, %29, %30, %31}, {%32, %33, %34, %35}, %36, p, 1, 1, 1;}\n"
    : "+f"(d[0]), "+f"(d[1]), "+f"(d[2]), "+f"(d[3]), "+f"(d[4]), "+f"(d[5]), "+f"(d[6]), "+f"(d[7]), "+f"(d[8]), "+f"(d[9]), "+f"(d[10]), "+f"(d[11]), "+f"(d[12]), "+f"(d[13]), "+f"(d[14]), "+f"(d[15]), "+f"(d[16]), "+f"(d[17]), "+f"(d[18]), "+f"(d[19]), "+f"(d[20]), "+f"(d[21]), "+f"(d[22]), "+f"(d[23]), "+f"(d[24]), "+f"(d[25]), "+f"(d[26]), "+f"(d[27]), "+f"(d[28]), "+f"(d[29]), "+f"(d[30]), "+f"(d[31]) : "r"(a0), "r"(a1), "r"(a2), "r"(a3), "l"(db), "r"(sc));
}

__device__ __forceinline__ float cosm(int m) { return __cosf((float)(((m + 1024) & 2047) - 1024) * 0.0030679615757712823f); }
constexpr int SIN = -512, NSIN = 512, NCOS = 1024;

template <bool AVG> __device__ __forceinline__ void ln2(float (&v)[2][16], float scale, float (&rs)[2], float (&of)[2]) {
  float s[2], q[2], p[2];
#pragma unroll
  for (int R = 0; R < 2; R++) {
    float a = v[R][0];
    if (AVG) {
      float b[4];
#pragma unroll
      for (int i = 0; i < 4; i++) b[i] = (v[R][4 * i] + v[R][4 * i + 1]) + (v[R][4 * i + 2] + v[R][4 * i + 3]);
      a = ((b[0] + b[1]) + (b[2] + b[3])) * 0.0625f;
    }
    p[R] = __shfl_sync(~0u, a, 0);
  }
#pragma unroll
  for (int R = 0; R < 2; R++) {
    float s0 = 0, s1 = 0, q0 = 0, q1 = 0;
#pragma unroll
    for (int i = 0; i < 16; i += 2) { const float a = v[R][i] -= p[R], b = v[R][i + 1] -= p[R]; s0 += a; s1 += b; q0 = fmaf(a, a, q0); q1 = fmaf(b, b, q1); }
    s[R] = s0 + s1; q[R] = q0 + q1;
  }
  {
    const int lane = threadIdx.x & 31;
    const bool u = lane & 16, u2 = lane & 8;
    float a = (u ? s[1] : s[0]) + __shfl_xor_sync(~0u, u ? s[0] : s[1], 16), b = (u ? q[1] : q[0]) + __shfl_xor_sync(~0u, u ? q[0] : q[1], 16);
    float c = (u2 ? b : a) + __shfl_xor_sync(~0u, u2 ? a : b, 8);
    c += __shfl_xor_sync(~0u, c, 4); c += __shfl_xor_sync(~0u, c, 2); c += __shfl_xor_sync(~0u, c, 1);
    s[0] = __shfl_sync(~0u, c, 0); q[0] = __shfl_sync(~0u, c, 8); s[1] = __shfl_sync(~0u, c, 16); q[1] = __shfl_sync(~0u, c, 24);
  }
#pragma unroll
  for (int R = 0; R < 2; R++) { const float d = s[R] * (1.f / 512.f); q[R] = fmaxf(q[R] - d * s[R], 0.f); s[R] = p[R] + d; }
#pragma unroll
  for (int R = 0; R < 2; R++) {
    float m = rbf(s[R]), r = rbf(rbf(q[R] * (1.f / 512.f)) + 1e-5f);
    asm("sqrt.approx.f32 %0, %0;" : "+f"(r));
    r = rbf(r);
    asm("rcp.approx.f32 %0, %0;" : "+f"(r));
    rs[R] = r * scale;
    of[R] = (p[R] - m) * rs[R];
  }
}

__global__ void __cluster_dims__(2, 1, 1) __launch_bounds__(384, 1)
fused_kernel(const __nv_bfloat16* __restrict__ x, const uint32_t* __restrict__ c_tab, Scratch* scr, const unsigned short* __restrict__ wr,
             const unsigned short* __restrict__ wi, __nv_bfloat16* __restrict__ out, const char* __restrict__ w1, const char* __restrict__ w2,
             const __grid_constant__ CUtensorMap tmW1, const __grid_constant__ CUtensorMap tmW2,
             const __grid_constant__ CUtensorMap tmA, const __grid_constant__ CUtensorMap tmO) {
  extern __shared__ char smem_raw[];
  uint32_t* const g_G = scr->G;
  __nv_bfloat16* const g_hn = scr->hn;
  unsigned* const g_cnt = scr->cnt;
  const uint32_t sb = (s2u(smem_raw) + 1023) & ~1023u;
  char* sm = smem_raw + (sb - s2u(smem_raw));
  const int tid = threadIdx.x, w = tid >> 5, lane = tid & 31, g = lane >> 2, t = lane & 3, j = blockIdx.x;
  asm volatile("{.reg .pred p; setp.eq.s32 p, %1, 256; @p prefetch.global.L2 [%0];}" ::"l"(c_tab + j * 32), "r"(tid));
  uint2 xr[2][4];
#pragma unroll
  for (int R = 0; R < 2; R++)
#pragma unroll
    for (int u = 0; u < 4; u++)
      asm volatile("{.reg .pred p; setp.lt.s32 p, %3, 8; @p ld.global.nc.v2.u32 {%0,%1}, [%2];}" : "=r"(xr[R][u].x), "=r"(xr[R][u].y)
                   : "l"(x + (size_t)(128 * (2 * w + R) + j) * 512 + 32 * (2 * t + (u & 1) + 8 * (u >> 1)) + 4 * g), "r"(w));
  const uint32_t fullW = sb + OFF_BAR, emptyW = fullW + 48, fullA = fullW + 96, emptyA = fullW + 144;
  const uint32_t fftDone = fullW + 192, tabA = fullW + 200, tabB = fullW + 208, wfFull = fullW + 216, wfDone = fullW + 224, go2 = fullW + 240, go1b = fullW + 248;
  const uint32_t rxFull = fullW + 256, txOk = fullW + 320;
  TS(0);
  if (__builtin_expect(w < 8, 1)) {
    const uint4* tab = (const uint4*)(sm + OFF_TAB) + lane;
#define TAB(G) tab[((G) < 17 ? (G) : (G) < 30 ? (G) - 2 : (G) - 6) * 32]
    const unsigned cnt0 = *(volatile unsigned*)(g_cnt + 32 * (j >> 3));
    TS(39);
    asm volatile("setmaxnreg.inc.sync.aligned.u32 232;");
    TS(52);
    uint32_t cc[4], sc[4], qr[2][4], qi[2][4];
#pragma unroll
    for (int r = 0; r < 4; r++) {
      const int k1 = g + 8 * (r & 1), m = k1 * (128 * (2 * t + 8 * (r >> 1)) + j);
      cc[r] = pk(cosm(m), cosm(m + 128 * k1)); sc[r] = pk(cosm(m + SIN), cosm(m + 128 * k1 + SIN));
#pragma unroll
      for (int v = 0; v < 2; v++) {
        const int m2 = (t + 4 * (r >> 1) + 8 * v) * (128 * k1 + j);
        const float c = cosm(m2), s = cosm(m2 + SIN);
        qr[v][r] = pk(c, -s); qi[v][r] = pk(s, c);
      }
    }
#pragma unroll
    for (int r = 0; r < 4; r++)
      asm volatile("" : "+r"(cc[r]), "+r"(sc[r]), "+r"(qr[0][r]), "+r"(qr[1][r]), "+r"(qi[0][r]), "+r"(qi[1][r]));
    TS(53);
    bar_sync(0, 384);
    const uint32_t tag = TAG3 | ((cnt0 >> 3) & 1);
    TS(1);
    {
      float v[2][16];
#pragma unroll
      for (int R = 0; R < 2; R++)
#pragma unroll
        for (int u = 0; u < 4; u++) { v[R][4 * u] = blo(xr[R][u].x); v[R][4 * u + 1] = bhi(xr[R][u].x); v[R][4 * u + 2] = blo(xr[R][u].y); v[R][4 * u + 3] = bhi(xr[R][u].y); }
      mbar_wait(tabA, 0);
      TS(2);
      float rs[2], of[2];
      ln2<true>(v, 1.f, rs, of);
      const uint4 fa = TAB(0);
      float d[4][2][4] = {};
#pragma unroll
      for (int q = 0; q < 4; q++)
#pragma unroll
        for (int R = 0; R < 2; R++) mma(d[q][R], fa, pk(v[R][q], v[R][4 + q]), pk(v[R][8 + q], v[R][12 + q]));
      uint32_t ar[4][2], ai[4][2], a8[4][2];
#pragma unroll
      for (int q = 0; q < 4; q++) {
        const float4 tw = asf(TAB(1 + q));
#pragma unroll
        for (int R = 0; R < 2; R++) {
          ar[q][R] = pk(d[q][R][0] * tw.x + d[q][R][2] * tw.z, d[q][R][1] * tw.y + d[q][R][3] * tw.w);
          a8[q][R] = pk(d[q][R][2] * tw.x - d[q][R][0] * tw.z, d[q][R][3] * tw.y - d[q][R][1] * tw.w);
          ai[q][R] = g == 0 ? 0u : a8[q][R];
        }
      }
      float re[4][4] = {}, im[4][4] = {}, er[2][4] = {}, ei[2][4] = {};
#pragma unroll
      for (int q = 0; q < 4; q++) {
        const uint4 b0 = TAB(5 + 2 * q), b1 = TAB(6 + 2 * q);
        mma(re[0], ar[q][0], ar[q][1], ai[q][0], ai[q][1], b0.x, b0.y);
        mma(im[0], ar[q][0], ar[q][1], ai[q][0], ai[q][1], b0.y ^ 0x80008000u, b0.x);
        mma(re[1], ar[q][0], ar[q][1], ai[q][0], ai[q][1], b0.z, b0.w);
        mma(im[1], ar[q][0], ar[q][1], ai[q][0], ai[q][1], b0.w ^ 0x80008000u, b0.z);
        mma(re[2], ar[q][0], ar[q][1], ai[q][0], ai[q][1], b1.x, b1.y);
        mma(im[2], ar[q][0], ar[q][1], ai[q][0], ai[q][1], b1.y, b1.x ^ 0x80008000u);
        mma(re[3], ar[q][0], ar[q][1], ai[q][0], ai[q][1], b1.z, b1.w);
        mma(im[3], ar[q][0], ar[q][1], ai[q][0], ai[q][1], b1.w, b1.z ^ 0x80008000u);
        if (q & 1) {
#pragma unroll
          for (int m = 0; m < 2; m++) {
            const uint4 b = TAB(13 + (q - 1) + m);
            mma(er[m], a8[q - 1][0], a8[q - 1][1], a8[q][0], a8[q][1], b.x, b.y);
            mma(ei[m], a8[q - 1][0], a8[q - 1][1], a8[q][0], a8[q][1], b.z, b.w);
          }
        }
      }
      TS(37);
      char* zs = sm + OFF_X;
#pragma unroll
      for (int R = 0; R < 2; R++)
#pragma unroll
        for (int m = 0; m < 2; m++) {
          uint2 a, b;
          const float c = rs[R];
          a.x = pk(c * (g == 0 ? er[m][2 * R] : re[m][2 * R]), c * (g == 0 ? er[m][2 * R + 1] : re[m][2 * R + 1]));
          a.y = pk(c * re[m + 2][2 * R], c * re[m + 2][2 * R + 1]);
          b.x = pk(c * (g == 0 ? ei[m][2 * R] : im[m][2 * R]), c * (g == 0 ? ei[m][2 * R + 1] : im[m][2 * R + 1]));
          b.y = pk(c * im[m + 2][2 * R], c * im[m + 2][2 * R + 1]);
          char* p = zs + (2 * w + R) * 528 + (32 * (4 * m + t) + 4 * g) * 2;
          *(uint2*)p = a; *(uint2*)(p + 16 * 528) = b;
        }
      bar_sync(1, 256);
      TS(38);
      uint32_t z[4][4];
#pragma unroll
      for (int nt = 0; nt < 4; nt++)
        asm volatile("ldmatrix.sync.aligned.m8n8.x4.trans.shared.b16 {%0,%1,%2,%3}, [%4];" : "=r"(z[nt][0]), "=r"(z[nt][1]), "=r"(z[nt][2]), "=r"(z[nt][3])
                     : "r"(sb + OFF_X + lane * 528 + (32 * w + 8 * nt) * 2) : "memory");
      float ur[4][4] = {}, ui[4][4] = {};
#pragma unroll
      for (int nt = 0; nt < 4; nt++) {
        mma(ur[nt], cc[0], cc[1], cc[2], cc[3], z[nt][0], z[nt][1]);
        mma(ui[nt], cc[0], cc[1], cc[2], cc[3], z[nt][2], z[nt][3]);
      }
#pragma unroll
      for (int nt = 0; nt < 4; nt++) {
        mma(ur[nt], sc[0], sc[1], sc[2], sc[3], z[nt][2], z[nt][3]);
        mma(ui[nt], sc[0] ^ 0x80008000u, sc[1] ^ 0x80008000u, sc[2] ^ 0x80008000u, sc[3] ^ 0x80008000u, z[nt][0], z[nt][1]);
      }
#pragma unroll
      for (int h = 0; h < 2; h++) {
        uint32_t* p = g_G + (((g + 8 * h) * 8 + w) * 128 + j) * 32 + 4 * t;
        st4(p, pk(ur[0][2 * h], ui[0][2 * h]), pk(ur[0][2 * h + 1], ui[0][2 * h + 1]), pk(ur[1][2 * h], ui[1][2 * h]), pk(ur[1][2 * h + 1], ui[1][2 * h + 1]), TAG1);
        st4(p + 16, pk(ur[2][2 * h], ui[2][2 * h]), pk(ur[2][2 * h + 1], ui[2][2 * h + 1]), pk(ur[3][2 * h], ui[3][2 * h]), pk(ur[3][2 * h + 1], ui[3][2 * h + 1]), TAG1);
      }
    }
    const long long tsend1 = clock64();
    TS(3);
    {
      mbar_wait(tabB, 0);
      const uint4 a0r = TAB(19), a0i = TAB(20), a1r = TAB(21), a1i = TAB(22), f8 = TAB(25), c16 = TAB(28), s16 = TAB(29), n16 = neg4(s16);
      const float4 fc = asf(TAB(23)), fs = asf(TAB(24)), ic = asf(TAB(26)), is = asf(TAB(27));
      TS(20);
      uint32_t z[4][4];
      mbar_wait(wfFull, 0);
      {
        const int i = lane >> 4, rem = (lane & 15) + 1, lam = (rem > 8 ? 4 * (16 - rem) + 2 : 4 * (rem & 7)) + i;
        const int pos = (lam & 16) + 4 * ((lam >> 1) & 3) + 2 * ((lam >> 3) & 1) + i;
        const unsigned short* raw = (const unsigned short*)(sm + OFF_WRAW) + w * 16 * 80 + (((j >> 3) * DF + 1) & 7) + lane;
        uint32_t f[16];
#pragma unroll
        for (int u = 0; u < 16; u++) f[u] = raw[u * 80] | ((uint32_t)raw[u * 80 + 40] << 16);
#pragma unroll
        for (int u = 0; u < 16; u++) *(uint32_t*)(sm + OFF_WF + (16 * w + u) * 128 + (((pos >> 2) ^ ((u ^ w) & 7)) << 4) + (pos & 3) * 4) = f[u];
      }
      TS(31);
      char* xs = sm + OFF_XS;
      const int lrow = tid >> 3, lch = tid & 7;
      delay(tsend1, DELAY1);
      poll_ld(z, g_G + j * 4096 + tid * 4, 1024, TAG1);
#pragma unroll
      for (int u = 0; u < 4; u++) *(uint4*)(xs + (lrow + 32 * u) * 128 + ((lch ^ ((lrow ^ (lrow >> 2)) & 7)) << 4)) = make_uint4(z[u][0], z[u][1], z[u][2], z[u][3]);
      bar_sync(1, 256);
      if (tid == 0) mbar_arrive(go1b);
#pragma unroll
      for (int u = 0; u < 4; u++) {
        const int row = 8 * t + g;
        const uint4 q = *(const uint4*)(xs + (row + 32 * u) * 128 + ((w ^ ((row ^ (row >> 2)) & 7)) << 4));
        z[u][0] = q.x; z[u][1] = q.y; z[u][2] = q.z; z[u][3] = q.w;
      }
      uint32_t wv[4][4];
#pragma unroll
      for (int r = 0; r < 4; r++) {
        const int k2 = g + 8 * (r >> 1) + 16 * (2 * t + (r & 1));
        const uint4 q = *(const uint4*)(sm + OFF_WF + k2 * 128 + ((w ^ ((k2 ^ (k2 >> 4)) & 7)) << 4));
        wv[0][r] = q.x; wv[1][r] = q.y; wv[2][r] = q.z; wv[3][r] = q.w;
      }
      TS(4);
      float vr[4][4] = {}, vi[4][4] = {};
#pragma unroll
      for (int c = 0; c < 4; c++) { mma(vr[c], a0r, z[0][c], z[1][c]); mma(vi[c], a0i, z[0][c], z[1][c]); }
#pragma unroll
      for (int c = 0; c < 4; c++) { mma(vr[c], a1r, z[2][c], z[3][c]); mma(vi[c], a1i, z[2][c], z[3][c]); }
      float xr_[4][4] = {}, xi_[4][4] = {};
#pragma unroll
      for (int c = 0; c < 4; c++) {
        const uint32_t a0 = pk(vr[c][0] * fc.x + vi[c][0] * fs.x, vr[c][1] * fc.y + vi[c][1] * fs.y), a1 = pk(vr[c][2] * fc.z + vi[c][2] * fs.z, vr[c][3] * fc.w + vi[c][3] * fs.w);
        const uint32_t a2 = pk(vi[c][0] * fc.x - vr[c][0] * fs.x, vi[c][1] * fc.y - vr[c][1] * fs.y), a3 = pk(vi[c][2] * fc.z - vr[c][2] * fs.z, vi[c][3] * fc.w - vr[c][3] * fs.w);
        mma(xr_[c], a0, a1, a2, a3, f8.x, f8.y); mma(xi_[c], a0, a1, a2, a3, f8.z, f8.x);
      }
      float d0[4][4] = {}, d1[4][4] = {};
#pragma unroll
      for (int c = 0; c < 4; c++) {
        const float scl = ((j & 7) == 7 && w == 1 && c == 1) ? 9.5367431640625e-07f : 1.9073486328125e-06f;
        float tr[4], ti[4];
#pragma unroll
        for (int r = 0; r < 4; r++) {
          const float a = blo(wv[c][r]) * scl, b = bhi(wv[c][r]) * scl;
          tr[r] = xr_[c][r] * a - xi_[c][r] * b; ti[r] = xr_[c][r] * b + xi_[c][r] * a;
        }
        mma(d0[c], f8.x, f8.y, f8.z, f8.x, pk(tr[0], tr[1]), pk(ti[0], ti[1]));
        mma(d1[c], f8.x, f8.y, f8.z, f8.x, pk(tr[2], tr[3]), pk(ti[2], ti[3]));
      }
      float yr[4][4] = {}, yi[4][4] = {};
      uint32_t bi[4][2];
#pragma unroll
      for (int c = 0; c < 4; c++) {
        const uint32_t br0 = pk(d0[c][0] * ic.x - d0[c][2] * is.x, d0[c][1] * ic.y - d0[c][3] * is.y);
        const uint32_t br1 = pk(d1[c][0] * ic.z - d1[c][2] * is.z, d1[c][1] * ic.w - d1[c][3] * is.w);
        bi[c][0] = pk(d0[c][0] * is.x + d0[c][2] * ic.x, d0[c][1] * is.y + d0[c][3] * ic.y);
        bi[c][1] = pk(d1[c][0] * is.z + d1[c][2] * ic.z, d1[c][1] * is.w + d1[c][3] * ic.w);
        mma(yr[c], c16, br0, br1); mma(yi[c], s16, br0, br1);
      }
#pragma unroll
      for (int c = 0; c < 4; c++) { mma(yr[c], n16, bi[c][0], bi[c][1]); mma(yi[c], c16, bi[c][0], bi[c][1]); }
      char* ys = sm + OFF_WRAW;
#pragma unroll
      for (int r = 0; r < 4; r++) {
        const int row = 8 * (g + 8 * (r >> 1)) + 2 * t + (r & 1);
        *(uint4*)(ys + row * 128 + ((w ^ ((row >> 1) & 7)) << 4)) = make_uint4(pk(yr[0][r], yi[0][r]), pk(yr[1][r], yi[1][r]), pk(yr[2][r], yi[2][r]), pk(yr[3][r], yi[3][r]));
      }
      bar_sync(1, 256);
#pragma unroll
      for (int u = 0; u < 4; u++) {
        const uint4 q = *(const uint4*)(ys + (lrow + 32 * u) * 128 + ((lch ^ ((lrow >> 1) & 7)) << 4));
        st4(g_G + j * 4096 + tid * 4 + 1024 * u, q.x, q.y, q.z, q.w, TAG2);
      }
      fence_async_s();
      mbar_arrive(wfDone);
    }
    const long long tsend2 = clock64();
    TS(5);
    uint32_t hq[2][2][4];
    {
      uint4 xq[2][2];
#pragma unroll
      for (int R = 0; R < 2; R++)
#pragma unroll
        for (int h = 0; h < 2; h++) xq[R][h] = __ldg((const uint4*)(x + (size_t)(128 * (2 * w + R) + j) * 512 + 32 * (g + 8 * h) + 8 * t));
      uint32_t z[4][4];
      delay(tsend2, DELAY2);
      poll_ld(z, g_G + ((t * 8 + w) * 128 + j) * 32 + 4 * g, 4 * 8 * 4096, TAG2);
      if (tid == 0) mbar_arrive(go2);
      TS(6);
      float vr[4][4] = {}, vi[4][4] = {};
#pragma unroll
      for (int c = 0; c < 4; c++) { mma(vr[c], qr[0][0], qr[0][1], qr[0][2], qr[0][3], z[0][c], z[1][c]); mma(vi[c], qi[0][0], qi[0][1], qi[0][2], qi[0][3], z[0][c], z[1][c]); }
#pragma unroll
      for (int c = 0; c < 4; c++) { mma(vr[c], qr[1][0], qr[1][1], qr[1][2], qr[1][3], z[2][c], z[3][c]); mma(vi[c], qi[1][0], qi[1][1], qi[1][2], qi[1][3], z[2][c], z[3][c]); }
      constexpr int XP = 36, XR = 8 * XP + 4;
      uint32_t* zs = (uint32_t*)(sm + OFF_X);
#pragma unroll
      for (int h = 0; h < 2; h++) {
        uint4* p = (uint4*)(zs + (g + 8 * h) * XR + XP * w + 8 * t);
        p[0] = make_uint4(pk(vr[0][2 * h], vi[0][2 * h]), pk(vr[1][2 * h], vi[1][2 * h]), pk(vr[2][2 * h], vi[2][2 * h]), pk(vr[3][2 * h], vi[3][2 * h]));
        p[1] = make_uint4(pk(vr[0][2 * h + 1], vi[0][2 * h + 1]), pk(vr[1][2 * h + 1], vi[1][2 * h + 1]), pk(vr[2][2 * h + 1], vi[2][2 * h + 1]), pk(vr[3][2 * h + 1], vi[3][2 * h + 1]));
      }
      bar_sync(1, 256);
      uint2 y[2][4], ye[2];
#pragma unroll
      for (int R = 0; R < 2; R++)
#pragma unroll
        for (int q = 0; q < 4; q++)
          y[R][q] = *(const uint2*)(zs + (2 * w + R) * XR + XP * (t + 4 * (q & 1)) + 16 * (g >> 2) + 8 * (g & 1) + 4 * (q >> 1) + (g & 2));
#pragma unroll
      for (int v = 0; v < 2; v++) {
        ye[v] = *(const uint2*)(zs + (2 * w + (g & 1)) * XR + XP * (t + 4 * v));
        if (g == 0) { y[0][v] = make_uint2(0, 0); y[1][v] = make_uint2(0, 0); }
      }
      float d[4][2][4] = {}, e[4][4] = {};
#pragma unroll
      for (int q = 0; q < 4; q++)
#pragma unroll
        for (int mu = 0; mu < 4; mu++) {
          const uint4 a = TAB(34 + 4 * mu + q);
          mma(d[mu][0], a, y[0][q].x, y[0][q].y); mma(d[mu][1], a, y[1][q].x, y[1][q].y);
          if (q < 2) mma(e[mu], a, ye[q].x, ye[q].y);
        }
      const float4 ec = asf(TAB(54)), es = asf(TAB(55));
      const uint4 l2 = TAB(56);
      float v[2][16];
#pragma unroll
      for (int mu = 0; mu < 4; mu++) {
        const float4 tw = asf(TAB(50 + mu));
        const float c8 = mu == 0 ? ec.x : mu == 1 ? ec.y : mu == 2 ? ec.z : ec.w, s8 = mu == 0 ? es.x : mu == 1 ? es.y : mu == 2 ? es.z : es.w;
#pragma unroll
        for (int R = 0; R < 2; R++) {
          float i0 = d[mu][R][0] * tw.z + d[mu][R][2] * tw.x;
          if (t == 0) i0 = e[mu][R] * c8 - e[mu][2 + R] * s8;
          float yy[4] = {0, 0, 0, 0};
          mma(yy, l2, pk(d[mu][R][0] * tw.x - d[mu][R][2] * tw.z, d[mu][R][1] * tw.y - d[mu][R][3] * tw.w), pk(i0, d[mu][R][1] * tw.w + d[mu][R][3] * tw.y));
          v[R][2 * mu] = yy[0]; v[R][2 * mu + 1] = yy[1]; v[R][8 + 2 * mu] = yy[2]; v[R][8 + 2 * mu + 1] = yy[3];
        }
      }
#pragma unroll
      for (int R = 0; R < 2; R++)
#pragma unroll
        for (int h = 0; h < 2; h++) {
          const uint32_t xs[4] = {xq[R][h].x, xq[R][h].y, xq[R][h].z, xq[R][h].w};
          uint32_t* hv = hq[R][h];
#pragma unroll
          for (int i = 0; i < 4; i++) {
            const uint32_t yb = pk(v[R][8 * h + 2 * i], v[R][8 * h + 2 * i + 1]);
            hv[i] = pk(blo(xs[i]) + blo(yb), bhi(xs[i]) + bhi(yb));
            v[R][8 * h + 2 * i] = blo(hv[i]); v[R][8 * h + 2 * i + 1] = bhi(hv[i]);
          }
        }
      TS(13);
      float rs[2], of[2];
      ln2<false>(v, 0.5f, rs, of);
#pragma unroll
      for (int R = 0; R < 2; R++)
#pragma unroll
        for (int i = 0; i < 16; i++) v[R][i] = fmaf(v[R][i], rs[R], of[R]);
#pragma unroll
      for (int h = 0; h < 2; h++)
#pragma unroll
        for (int R = 0; R < 2; R++) {
          const bool tg = h == 0 && g < 2 * NA;
          uint32_t* p = tg ? g_G + (((2 * w + R) * 8 + (g >> 1)) * 128 + j) * 32 + 16 * (g & 1) + 4 * t
                           : (uint32_t*)(g_hn + (size_t)(128 * (2 * w + R) + j) * 512 + 32 * (g + 8 * h) + 8 * t);
          const uint32_t p0 = pk(v[R][8 * h], v[R][8 * h + 1]);
          st4(p, p0, pk(v[R][8 * h + 2], v[R][8 * h + 3]), pk(v[R][8 * h + 4], v[R][8 * h + 5]), pk(v[R][8 * h + 6], v[R][8 * h + 7]), tg ? tag : p0 & TAGM);
        }
    }
    const long long tsend3 = clock64();
    TS(14);
    fence_async_g();
    bar_sync(7, 288);
    TS(7);
    const int wg = w >> 2;
    const uint32_t abase = sb + OFF_A + wg * NA * ASLOT;
    const int rho = (tid & 127) >> 3, ch = tid & 7;
    const uint32_t* ap = g_G + ((8 * wg + (rho >> 3)) * 8 * 128 + (j & ~7) + (rho & 7)) * 32 + 4 * ch;
    uint32_t za[NA][4][4];
    delay(tsend3, DELAY3 + wg * DELAY4);
#pragma unroll
    for (int k = 0; k < NA; k++) ld4(za[k], ap + 4096 * k, 2 * 8 * 4096);
#pragma unroll
    for (int k = 0; k < NA; k++) {
      if (stale(za[k], tag)) poll_ld(za[k], ap + 4096 * k, 2 * 8 * 4096, tag);
#pragma unroll
      for (int u = 0; u < 4; u++)
        asm volatile("st.shared.v4.u32 [%0], {%1,%2,%3,%4};" ::"r"(abase + k * ASLOT + (rho + 16 * u) * 128 + ((ch ^ (rho & 7)) << 4)),
                     "r"(za[k][u][0]), "r"(za[k][u][1]), "r"(za[k][u][2]), "r"(za[k][u][3]) : "memory");
    }
    TS(16);
    fence_async_s();
    if (wg == 0) bar_sync(2, 128); else bar_sync(4, 256);
    uint32_t hf[56];
    float o2[2][64], o3[2][32];
    {
      float acc[112];
#pragma unroll
      for (int k = 0; k < 8; k++) {
        if (k == NA) {
          wg_wait<0>();
          if ((tid & 127) == 0) { mbar_arrive(emptyW + 8 * ((k - 1) % NW)); mbar_arrive(emptyA + 8 * (wg * NA + (k - 1) % NA)); }
        }
        if (k >= NA) mbar_wait(fullA + 8 * (wg * NA + k % NA), (k / NA - 1) & 1);
        mbar_wait(fullW + 8 * (k % NW), k / NW);
        if (k == RL1 && wg == 1) bar_sync(3, 256);
        if (k == 0) { TS(8); TW(23); } else { TS(23 + k); TW(55 + k); }
        wg_fence();
#pragma unroll
        for (int kk = 0; kk < 4; kk++)
          wgmma_ss_n224(acc, mkdesc(abase + (k % NA) * ASLOT + kk * 32, 16, 1024, 1),
                        mkdesc(sb + (k % NW) * WSLOT + kk * 1024, 4096, 512, 2), (k | kk) != 0);
        wg_commit();
        if (k == LAG - 1 && wg == 0) asm volatile("bar.arrive 4, 256;" ::: "memory");
        if (k == RL0 && wg == 0) asm volatile("bar.arrive 3, 256;" ::: "memory");
        if (k == HS) {
#pragma unroll
          for (int R = 0; R < 2; R++)
#pragma unroll
            for (int h = 0; h < 2; h++)
              st4((uint32_t*)(out + (size_t)(128 * (2 * w + R) + j) * 512 + 32 * (g + 8 * h) + 8 * t), hq[R][h][0], hq[R][h][1], hq[R][h][2], hq[R][h][3], hq[R][h][0] & TAGM);
        }
        if (k == HS + 2) { fence_async_g(); asm volatile("bar.arrive 5, 288;" ::: "memory"); }
        if (k > 0 && k != NA) {
          wg_wait<1>();
          if ((tid & 127) == 0) { mbar_arrive(emptyW + 8 * ((k - 1) % NW)); mbar_arrive(emptyA + 8 * (wg * NA + (k - 1) % NA)); }
        }
      }
      wg_wait<0>();
      keep(acc);
      if ((tid & 127) == 0) { mbar_arrive(emptyW + 8 * (7 % NW)); rem_arrive(peer(txOk + 16 * wg)); }
      TS(9); TW(21);
      mbar_wait(fullW + 8 * (8 % NW), 1);
      mbar_wait(fullW + 8 * (9 % NW), 1);
#pragma unroll
      for (int k0 = 0; k0 < 14; k0 += SG) {
#pragma unroll
        for (int i = 4 * k0; i < 4 * k0 + 4 * SG; i++) {
          const float a = acc[2 * i], b = acc[2 * i + 1];
          float ta, tb;
          asm volatile("tanh.approx.f32 %0, %1;" : "=f"(ta) : "f"(a));
          asm volatile("tanh.approx.f32 %0, %1;" : "=f"(tb) : "f"(b));
          hf[i] = pk(fmaf(a, ta, a), fmaf(b, tb, b));
        }
        wg_fence();
#pragma unroll
        for (int kk = k0; kk < k0 + SG; kk++)
          wgmma_rs_n128(o2[0], hf[4 * kk], hf[4 * kk + 1], hf[4 * kk + 2], hf[4 * kk + 3], mkdesc(sb + (8 % NW) * WSLOT + kk * 2048, WSLOT, 1024, 1), kk != 0);
      }
      wg_commit();
      if (wg == 1) asm volatile("bar.arrive 6, 256;" ::: "memory");
    }
    TS(10); TW(22);
    const uint32_t rxw = abase + (w & 3) * 2048 + lane * 16, prx = peer(rxw), pfull = peer(rxFull + 32 * wg);
    auto send = [&](const float* a, int i) {
#pragma unroll
      for (int u = 0; u < 4; u++)
        asm volatile("st.async.weak.shared::cluster.mbarrier::complete_tx::bytes.v4.b32 [%0], {%1,%2,%3,%4}, [%5];" ::"r"(prx + (i % NA) * ASLOT + u * 512),
                     "r"(pk(a[8 * u], a[8 * u + 1])), "r"(pk(a[8 * u + 2], a[8 * u + 3])), "r"(pk(a[8 * u + 4], a[8 * u + 5])), "r"(pk(a[8 * u + 6], a[8 * u + 7])), "r"(pfull + 8 * i) : "memory");
    };
    uint4 q[4];
    auto recv = [&](int i) {
      mbar_wait(rxFull + 32 * wg + 8 * i, 0);
#pragma unroll
      for (int u = 0; u < 4; u++)
        asm volatile("ld.shared.v4.u32 {%0,%1,%2,%3}, [%4];" : "=r"(q[u].x), "=r"(q[u].y), "=r"(q[u].z), "=r"(q[u].w) : "r"(rxw + (i % NA) * ASLOT + u * 512) : "memory");
    };
    auto own = [&](const float* a, int i) {
      const uint32_t stg = abase + (i % NA) * ASLOT;
      const int row = 16 * (w & 3) + (lane & 15);
      __syncwarp();
#pragma unroll
      for (int u = 0; u < 4; u++)
        asm volatile("stmatrix.sync.aligned.m8n8.x4.shared.b16 [%0], {%1,%2,%3,%4};" ::"r"(stg + row * 128 + (((2 * u + (lane >> 4)) ^ (row & 7)) << 4)),
                     "r"(add2(pk(a[8 * u], a[8 * u + 1]), q[u].x)), "r"(add2(pk(a[8 * u + 2], a[8 * u + 3]), q[u].y)),
                     "r"(add2(pk(a[8 * u + 4], a[8 * u + 5]), q[u].z)), "r"(add2(pk(a[8 * u + 6], a[8 * u + 7]), q[u].w)) : "memory");
      fence_async_s();
      asm volatile("bar.arrive %0, 160;" ::"r"(8 + 4 * wg + i) : "memory");
    };
    auto mm = [&](int c, int k0, int k1) {
      if (k0 == 0) {
        mbar_wait(fullW + 8 * ((8 + 2 * c) % NW), ((8 + 2 * c) / NW) & 1);
        mbar_wait(fullW + 8 * ((9 + 2 * c) % NW), ((9 + 2 * c) / NW) & 1);
      }
      wg_fence();
#pragma unroll
      for (int kk = k0; kk < k1; kk++)
        wgmma_rs_n128(o2[c & 1], hf[4 * kk], hf[4 * kk + 1], hf[4 * kk + 2], hf[4 * kk + 3],
                      mkdesc(sb + ((8 + 2 * c) % NW) * WSLOT + kk * 2048, WSLOT, 1024, 1), kk != 0);
      wg_commit();
    };
    auto mh = [&](int h) {
      mbar_wait(fullW + 8 * ((14 + h) % NW), 0);
      wg_fence();
#pragma unroll
      for (int kk = 0; kk < 14; kk++)
        wgmma_rs_n64(o3[h], hf[4 * kk], hf[4 * kk + 1], hf[4 * kk + 2], hf[4 * kk + 3],
                     mkdesc(sb + ((14 + h) % NW) * WSLOT + kk * 2048, 16, 1024, 1), kk != 0);
      wg_commit();
    };
    mm(1, 0, 7);
    wg_wait<1>(); keep(o2[0]);
    TS(32); TW(48);
    if ((tid & 127) == 0) { mbar_arrive(emptyW + 8 * (8 % NW)); mbar_arrive(emptyW + 8 * (9 % NW)); }
    mbar_wait(txOk + 16 * wg, 0);
    send(o2[0], 0);
    mm(1, 7, 14);
    send(o2[0] + 32, 1);
    TS(40); TW(44);
    if (wg == 0) bar_sync(6, 256);
    mm(2, 0, 7);
    recv(0);
    wg_wait<1>(); keep(o2[1]);
    TS(33); TW(49);
    own(o2[1], 0);
    mm(2, 7, 14);
    send(o2[1] + 32, 2);
    TS(41); TW(45);
    recv(1);
    mh(0);
    wg_wait<1>(); keep(o2[0]);
    TS(34); TW(50);
    own(o2[0], 1);
    recv(2);
    mbar_wait(txOk + 16 * wg + 8, 0);
    own(o2[0] + 32, 2);
    wg_wait<0>(); keep(o3[0]);
    send(o3[0], 3);
    mh(1);
    TS(42); TW(46);
    TW(63);
    recv(3);
    wg_wait<0>(); keep(o3[1]);
    TS(35); TW(51);
    own(o3[1], 3);
    TS(43); TW(47);
    TS(11);
  } else {
    const long long tstart = clock64();
    if (tid == 288) {
      mbar_init(tabA, 1); mbar_init(tabB, 1);
      fence_async_s();
      mbar_expect(tabA, NG_P1 * 512);
      asm volatile("cp.async.bulk.shared::cluster.global.mbarrier::complete_tx::bytes [%0], [%1], %2, [%3];" ::"r"(sb + OFF_TAB), "l"(c_tab), "r"(NG_P1 * 512), "r"(tabA) : "memory");
      mbar_expect(tabB, (NG_ALL - NG_P1) * 512);
      asm volatile("cp.async.bulk.shared::cluster.global.mbarrier::complete_tx::bytes [%0], [%1], %2, [%3];" ::"r"(sb + OFF_TAB + NG_P1 * 512), "l"(c_tab + NG_P1 * 128), "r"((NG_ALL - NG_P1) * 512), "r"(tabB) : "memory");
    }
    __syncwarp();
    if (tid == 288) TSX(55);
    asm volatile("setmaxnreg.dec.sync.aligned.u32 40;");
    const int r = j & 7;
    unsigned tgt3 = 0;
    if (tid == 256) {
      for (int i = 0; i < NW; i++) { mbar_init(fullW + 8 * i, 1); mbar_init(emptyW + 8 * i, 2); mbar_init(fullA + 8 * i, 1); mbar_init(emptyA + 8 * i, 1); }
      mbar_init(fftDone, 1); mbar_init(wfFull, 1); mbar_init(wfDone, 256); mbar_init(go2, 1); mbar_init(go1b, 1);
      for (int i = 0; i < 12; i++) mbar_init(rxFull + 8 * i, 1);
      asm volatile("fence.mbarrier_init.release.cluster;" ::: "memory");
      for (int i = 0; i < 8; i++) mbar_expect(rxFull + 8 * i, ASLOT);
    }
    __syncwarp();
    if (tid == 256) TSX(54);
    asm volatile("bar.arrive 0, 384;" ::: "memory");
    {
      const int e0 = (j >> 3) * DF + 32 * r + 1, mis = e0 & 7;
      delay(tstart, DELAY0);
#pragma unroll
      for (int n = 0; n < 5; n++) {
        const int i = lane + 32 * n, k2 = 32 * (w - 8) + i / 5, u = i % 5;
        if (u < 4 || mis) {
          asm volatile("cp.async.cg.shared.global [%0], [%1], 16;" ::"r"(sb + OFF_WRAW + k2 * 160 + u * 16), "l"(wr + e0 - mis + k2 * 16 * DF + u * 8) : "memory");
          asm volatile("cp.async.cg.shared.global [%0], [%1], 16;" ::"r"(sb + OFF_WRAW + k2 * 160 + 80 + u * 16), "l"(wi + e0 - mis + k2 * 16 * DF + u * 8) : "memory");
        }
      }
      if (tid == 352) {
        delay(tstart, DELAY5);
        asm volatile("cp.async.bulk.prefetch.L2.global [%0], %1;" ::"l"(w1 + j * 14336), "r"(14336) : "memory");
        asm volatile("cp.async.bulk.prefetch.L2.global [%0], %1;" ::"l"(w2 + j * 14336), "r"(14336) : "memory");
      }
      __syncwarp();
      tgt3 = (*(volatile unsigned*)(g_cnt + 32 * (j >> 3)) & ~7u) + 8;
      asm volatile("cp.async.wait_all;" ::"r"(tgt3) : "memory");
    }
    bar_sync(5, 128);
    if (tid == 256) mbar_arrive(wfFull);
    if (tid == 256) TSX(19);
    if (tid == 256) {
      asm volatile("prefetch.tensormap [%0];" ::"l"(&tmW1) : "memory");
      asm volatile("prefetch.tensormap [%0];" ::"l"(&tmW2) : "memory");
      asm volatile("prefetch.tensormap [%0];" ::"l"(&tmA) : "memory");
      asm volatile("prefetch.tensormap [%0];" ::"l"(&tmO) : "memory");
      mbar_wait(go1b, 0);
      for (int i = 0; i < 2; i++) { mbar_expect(fullW + 8 * i, WSLOT); tma3(sb + i * WSLOT, &tmW1, 0, 64 * i, 7 * r, fullW + 8 * i); }
      mbar_wait(wfDone, 0);
      mbar_wait(go2, 0);
#pragma unroll
      for (int idx = 2; idx < 16; idx++) {
        const int s = idx % NW;
        if (idx >= NW) mbar_wait(emptyW + 8 * s, (idx / NW - 1) & 1);
        mbar_expect(fullW + 8 * s, WSLOT);
        if (idx < 8) tma3(sb + s * WSLOT, &tmW1, 0, 64 * idx, 7 * r, fullW + 8 * s);
        else {
          const int c = idx - 8, mine = (0xB4 >> c) & 1, i = (0xF984 >> (2 * c)) & 3;
          tma2(sb + s * WSLOT, &tmW2, 64 * ((2 * i + (mine ? j : j ^ 1)) & 7), 224 * r, fullW + 8 * s);
        }
      }
    } else if (w == 9 || w == 10) {
      const int wg = w - 9;
      if (lane == 0) {
        mbar_wait(fftDone, 0);
        poll(g_cnt + 32 * (j >> 3), tgt3);
        fence_async_g();
        TSX(17 + wg);
#pragma unroll
        for (int k = NA; k < 8; k++) {
          const uint32_t s = wg * NA + k % NA;
          mbar_wait(emptyA + 8 * s, (k / NA - 1) & 1);
          mbar_expect(fullA + 8 * s, ASLOT);
          tma3(sb + OFF_A + s * ASLOT, &tmA, 64 * k, j & ~7, 8 * wg, fullA + 8 * s);
        }
        poll(g_cnt + 32 * (16 + (j >> 3)), tgt3);
        fence_async_g();
      }
#pragma unroll
      for (int i = 0; i < 4; i++) {
        __syncwarp();
        bar_sync(8 + 4 * wg + i, 160);
        if (lane == 0) {
          asm volatile("cp.reduce.async.bulk.tensor.3d.global.shared::cta.add.bulk_group [%0, {%2, %3, %4}], [%1];"
                       ::"l"(&tmO), "r"(sb + OFF_A + (wg * NA + i % NA) * ASLOT), "r"(64 * ((2 * i + j) & 7)), "r"(j & ~7), "r"(8 * wg) : "memory");
          asm volatile("cp.async.bulk.commit_group;" ::: "memory");
          if (i == 0) { asm volatile("cp.async.bulk.wait_group.read 0;" ::: "memory"); rem_arrive(peer(txOk + 16 * wg + 8)); }
        }
      }
      if (lane == 0) asm volatile("cp.async.bulk.wait_group.read 0;" ::: "memory");
    } else if (w == 11) {
      bar_sync(7, 288);
      if (lane == 0) {
        red_rel(g_cnt + 32 * (j >> 3));
        mbar_arrive(fftDone);
      }
      __syncwarp();
      bar_sync(5, 288);
      if (lane == 0) red_rel(g_cnt + 32 * (16 + (j >> 3)));
    }
  }
}

typedef CUresult (*EncodeFn)(CUtensorMap*, CUtensorMapDataType, cuuint32_t, void*, const cuuint64_t*, const cuuint64_t*, const cuuint32_t*,
                             const cuuint32_t*, CUtensorMapInterleave, CUtensorMapSwizzle, CUtensorMapL2promotion, CUtensorMapFloatOOBfill);
void encode(EncodeFn fn, CUtensorMap* m, void* p, int rank, const cuuint64_t* dims, const cuuint64_t* strides, const cuuint32_t* box, CUtensorMapSwizzle sw) {
  const cuuint32_t es[3] = {1, 1, 1};
  fn(m, CU_TENSOR_MAP_DATA_TYPE_BFLOAT16, rank, p, dims, strides, box, es, CU_TENSOR_MAP_INTERLEAVE_NONE, sw,
     CU_TENSOR_MAP_L2_PROMOTION_L2_128B, CU_TENSOR_MAP_FLOAT_OOB_FILL_NONE);
}
}

extern "C" void kernel_launch(void* const* d_in, const int* in_sizes, int n_in, void* d_out, int out_size) {
  (void)in_sizes; (void)n_in; (void)out_size;
  void* fnp = nullptr;
  cudaDriverEntryPointQueryResult qr;
  cudaGetDriverEntryPoint("cuTensorMapEncodeTiled", &fnp, cudaEnableDefault, &qr);
  EncodeFn fn = (EncodeFn)fnp;
  void *hn = nullptr, *tab = nullptr;
  cudaGetSymbolAddress(&hn, g_scr);
  cudaGetSymbolAddress(&tab, g_tab);
  CUtensorMap tW1, tW2, tA, tO;
  { const cuuint64_t d[3] = {32, 512, 56}, s[2] = {3584, 64}; const cuuint32_t b[3] = {32, 64, 7}; encode(fn, &tW1, d_in[4], 3, d, s, b, CU_TENSOR_MAP_SWIZZLE_64B); }
  { const cuuint64_t d[2] = {512, 1792}, s[1] = {1024}; const cuuint32_t b[2] = {64, 224}; encode(fn, &tW2, d_in[5], 2, d, s, b, CU_TENSOR_MAP_SWIZZLE_128B); }
  { const cuuint64_t d[3] = {512, 128, 16}, s[2] = {1024, 131072}; const cuuint32_t b[3] = {64, 8, 8}; encode(fn, &tA, hn, 3, d, s, b, CU_TENSOR_MAP_SWIZZLE_128B); }
  { const cuuint64_t d[3] = {512, 128, 16}, s[2] = {1024, 131072}; const cuuint32_t b[3] = {64, 8, 8}; encode(fn, &tO, d_out, 3, d, s, b, CU_TENSOR_MAP_SWIZZLE_128B); }
  cudaFuncSetAttribute(fused_kernel, cudaFuncAttributeMaxDynamicSharedMemorySize, SMEM_BYTES);
  fused_kernel<<<NCTA, 384, SMEM_BYTES>>>((const __nv_bfloat16*)d_in[0], (const uint32_t*)tab, (Scratch*)hn, (const unsigned short*)d_in[1], (const unsigned short*)d_in[2],
                                          (__nv_bfloat16*)d_out, (const char*)d_in[4], (const char*)d_in[5], tW1, tW2, tA, tO);
}
```
